```python
import torch

def _softmax(x, axis=-1):
    return torch.softmax(x, dim=axis)

def _gelu(x):
    return torch.nn.functional.gelu(x, approximate='tanh')

def _silu(x):
    return torch.nn.functional.silu(x)

def _sigmoid(x):
    return torch.sigmoid(x)

def _layernorm(x, axis=-1, eps=1e-05):
    m = x.mean(dim=axis, keepdim=True)
    v = x.var(dim=axis, keepdim=True, unbiased=False)
    return (x - m) / torch.sqrt(v + eps)

def _scatter_add(tgt, idx, src, axis=0):
    return tgt.clone().index_add_(axis, idx, src)

def _segment_sum(src, seg, n):
    out = torch.zeros((n,) + src.shape[1:], dtype=src.dtype)
    return out.index_add_(0, seg, src)

def _pad(x, pw):
    flat = tuple((v for pair in reversed(pw) for v in pair))
    return torch.nn.functional.pad(x, flat)
kernel_name = 'adaLN_cond__spectral_fnet__glu_gated_glu__prompt'

def setup_inputs():

    _w = lambda a: (lambda t: t.to(torch.bfloat16) if t.is_floating_point() else t)(torch.as_tensor(a))

    def _A_setup():
        B, S, D = (1, 2048, 512)
        ns = torch.arange(S)[:, None] * torch.arange(S)[None, :]
        nd = torch.arange(D)[:, None] * torch.arange(D)[None, :]
        Ws_re = torch.cos(-2.0 * torch.pi * ns / S).to(float)
        Ws_im = torch.sin(-2.0 * torch.pi * ns / S).to(float)
        Wd_re = torch.cos(-2.0 * torch.pi * nd / D).to(float)
        Wd_im = torch.sin(-2.0 * torch.pi * nd / D).to(float)
        return {'x': _w((lambda *s: torch.randn(*s, dtype=torch.bfloat16) * 0.05)(B, S, D)), 'dft_seq_re': _w(Ws_re), 'dft_seq_im': _w(Ws_im), 'dft_hid_re': _w(Wd_re), 'dft_hid_im': _w(Wd_im)}
    _A_in = _A_setup()

    def _B_setup():
        B, S, D, F = (1, 2048, 512, 1376)
        return {'x': _w((lambda *s: torch.randn(*s, dtype=torch.bfloat16) * 0.05)(B, S, D)), 'w_gate': _w((lambda *s: torch.randn(*s, dtype=torch.bfloat16) * 3.2)(D, F)), 'w_up': _w((lambda *s: torch.randn(*s, dtype=torch.bfloat16) * 3.2)(D, F)), 'w_down': _w((lambda *s: torch.randn(*s, dtype=torch.bfloat16) * 3.2)(F, D))}
    _B_in = _B_setup()
    return {'A_x': _A_in['x'], 'A_dft_seq_re': _A_in['dft_seq_re'], 'A_dft_seq_im': _A_in['dft_seq_im'], 'A_dft_hid_re': _A_in['dft_hid_re'], 'A_dft_hid_im': _A_in['dft_hid_im'], 'B_x': _B_in['x'], 'B_w_gate': _B_in['w_gate'], 'B_w_up': _B_in['w_up'], 'B_w_down': _B_in['w_down'], 'c': _w((lambda *s: torch.randn(*s, dtype=torch.bfloat16) * 0.2)(1, 512) * 8.0), 'w_mod': _w((lambda *s: torch.randn(*s, dtype=torch.bfloat16) * 0.2)(512, 6 * 512) * 512 ** (-0.5) * 8.0)}

def reference(A_x, A_dft_seq_re, A_dft_seq_im, A_dft_hid_re, A_dft_hid_im, B_x, B_w_gate, B_w_up, B_w_down, c, w_mod):

    def _A_ref(x, dft_seq_re, dft_seq_im, dft_hid_re, dft_hid_im):
        a = torch.einsum('bsd,ed->bse', x, dft_hid_re)
        b = torch.einsum('bsd,ed->bse', x, dft_hid_im)
        y = torch.einsum('ts,bse->bte', dft_seq_re, a) - torch.einsum('ts,bse->bte', dft_seq_im, b)
        return y

    def _B_ref(x, w_gate, w_up, w_down):
        g = torch.einsum('bsd,df->bsf', x, w_gate)
        u = torch.einsum('bsd,df->bsf', x, w_up)
        h = _sigmoid(g) * u
        return torch.einsum('bsf,fd->bsd', h, w_down)
    x = A_x
    mod = (_silu(c) @ w_mod).reshape(c.shape[0], 6, 1, -1)
    sa, ca, ga, sb, cb, gb = (mod[:, 0].clone(), mod[:, 1].clone(), mod[:, 2].clone(), mod[:, 3].clone(), mod[:, 4].clone(), mod[:, 5].clone())
    h = _layernorm(x, axis=-1) * (1 + ca) + sa
    x = x + ga * _A_ref(h, A_dft_seq_re, A_dft_seq_im, A_dft_hid_re, A_dft_hid_im)
    h = _layernorm(x, axis=-1) * (1 + cb) + sb
    x = x + gb * _B_ref(h, B_w_gate, B_w_up, B_w_down)
    return x
```

```cpp
#include <cuda_runtime.h>
#include <cuda_bf16.h>
#include <cuda.h>
#include <stdint.h>

#define EXP_MOD 1
#define EXP_CS 1
#define EXP_LDSM 1
namespace {

constexpr int S_ = 2048, D_ = 512, F_ = 1376;
constexpr int NCTA = 128;
constexpr int NB = 9;
constexpr int NA = 4;
constexpr int NA1 = 6;
constexpr int NB1 = 7;
constexpr uint32_t OFF_B = 0;
constexpr uint32_t OFF_A = NB * 16384;
constexpr uint32_t OFF_AUX = OFF_A + 2 * NA * 8192;
constexpr uint32_t OFF_ONES = OFF_AUX;
constexpr uint32_t OFF_CA1 = OFF_ONES + 1024;
constexpr uint32_t OFF_SA = OFF_CA1 + 128 * 4;
constexpr uint32_t OFF_GA = OFF_SA + 128 * 4;
constexpr uint32_t OFF_CB1 = OFF_GA + 64 * 4;
constexpr uint32_t OFF_GB = OFF_CB1 + 64 * 4;
constexpr uint32_t OFF_T3 = OFF_GB + 64 * 4;
constexpr uint32_t OFF_ST = OFF_T3 + 88 * 8 * 4;
constexpr uint32_t OFF_RSP = OFF_ST + 1024;
constexpr uint32_t OFF_PUB = OFF_RSP + 512;
constexpr uint32_t OFF_RED = OFF_PUB + 512;
constexpr uint32_t OFF_WM = OFF_RED + 2048;
constexpr uint32_t OFF_BAR = OFF_WM + 8192;
constexpr uint32_t BAR_FULLB = OFF_BAR;
constexpr uint32_t BAR_EMPTYB = BAR_FULLB + 8 * NB;
constexpr uint32_t BAR_PEMPTYB = BAR_EMPTYB + 8 * NB;
constexpr uint32_t BAR_FULLA = BAR_PEMPTYB + 8 * NB;
constexpr uint32_t BAR_EMPTYA = BAR_FULLA + 16 * NA1;
constexpr uint32_t BAR_PEMPTYA = BAR_EMPTYA + 16 * NA1;
constexpr uint32_t BAR_MISC = BAR_PEMPTYA + 16 * NA1;
constexpr uint32_t BAR_PRDY = BAR_MISC;
constexpr uint32_t BAR_RFULL = BAR_PRDY + 16;
constexpr uint32_t BAR_AUX = BAR_RFULL + 16;
constexpr uint32_t BAR_XARR = BAR_AUX + 24;
constexpr uint32_t BAR_WM = BAR_XARR + 8;
constexpr uint32_t SMEM_USED = BAR_WM + 16;
constexpr uint32_t SMEM_BYTES = SMEM_USED;
static_assert(SMEM_BYTES <= 232448, "smem");
constexpr int NKB4 = 11;
constexpr uint32_t P2_SLOTS = 4u | (5u << 4) | (6u << 8) | (0u << 12) | (7u << 16) | (8u << 20) | (1u << 24) | (2u << 28);

enum { M_WRE = 0, M_WIM, M_XN, M_PQ, M_DR, M_DI, M_Z, M_WG, M_WU, M_HLD, M_HST, M_WD, M_OUT, M_WMOD, M_WG32, M_WU32, M_COUNT };

struct alignas(64) Params {
    const __nv_bfloat16* x;
    const __nv_bfloat16* c;
    const __nv_bfloat16* wmod;
    const __nv_bfloat16* wg;
    const __nv_bfloat16* wu;
    const __nv_bfloat16* dr;
    const __nv_bfloat16* di;
    const __nv_bfloat16* wd;
    const __nv_bfloat16* wre;
    const __nv_bfloat16* wim;
    const void* pad[6];
    CUtensorMap m[M_COUNT];
};

constexpr int CN_X = 0;
constexpr int CN_MOD = 8;
constexpr int CN_V = 10;
constexpr int CN_CS = 12;
constexpr int CN_1 = 16;
constexpr int CN_2 = CN_1 + 64;
constexpr int CN_3 = CN_2 + 32;
constexpr int CN_COUNT = CN_3 + 64;

}

__device__ __align__(1024) __nv_bfloat16 g_xn[S_ * D_];
__device__ __align__(1024) __nv_bfloat16 g_pq[S_ * 2 * D_];
__device__ __align__(1024) __nv_bfloat16 g_z[S_ * D_];
__device__ __align__(1024) __nv_bfloat16 g_h[S_ * F_];
__device__ __align__(1024) uint4 g_x2s[NCTA * 2 * 4 * 128];
__device__ __align__(1024) float2 g_stats[S_ * 8];
__device__ __align__(1024) float g_mod[6 * D_];
__device__ __align__(1024) float g_cs[4 * F_];
__device__ __align__(1024) float g_v[2 * D_];
__device__ __align__(1024) float g_rs[32 * 4 * 128];
__device__ __align__(1024) unsigned g_cnt[CN_COUNT * 32];
__device__ unsigned g_epoch;
__device__ unsigned g_done;
#define TRACE_INIT() do {} while (0)
#define TRACE(slot) do {} while (0)
#define TRACE2(ev, idx) do {} while (0)
#define TRACE_GT(slot) do {} while (0)

namespace {

__device__ __forceinline__ uint32_t smem_u32(const void* p) { return (uint32_t)__cvta_generic_to_shared(p); }
__device__ __forceinline__ void mbar_init(uint32_t bar, uint32_t cnt) { asm volatile("mbarrier.init.shared::cta.b64 [%0], %1;" :: "r"(bar), "r"(cnt) : "memory"); }
__device__ __forceinline__ void mbar_expect_tx(uint32_t bar, uint32_t bytes) { asm volatile("mbarrier.arrive.expect_tx.shared::cta.b64 _, [%0], %1;" :: "r"(bar), "r"(bytes) : "memory"); }
__device__ __forceinline__ void mbar_arrive(uint32_t bar) { asm volatile("mbarrier.arrive.shared::cta.b64 _, [%0];" :: "r"(bar) : "memory"); }
__device__ __forceinline__ void mbar_arrive_n(uint32_t bar, uint32_t n) { asm volatile("mbarrier.arrive.shared::cta.b64 _, [%0], %1;" :: "r"(bar), "r"(n) : "memory"); }
__device__ __forceinline__ uint32_t mapa(uint32_t addr, uint32_t cta) { uint32_t r; asm volatile("mapa.shared::cluster.u32 %0, %1, %2;" : "=r"(r) : "r"(addr), "r"(cta)); return r; }
__device__ __forceinline__ void mbar_arrive_cl(uint32_t cl_addr) { asm volatile("mbarrier.arrive.shared::cluster.b64 _, [%0];" :: "r"(cl_addr) : "memory"); }
__device__ __forceinline__ void mbar_arrive_cl_n(uint32_t cl_addr, uint32_t n) { asm volatile("mbarrier.arrive.shared::cluster.b64 _, [%0], %1;" :: "r"(cl_addr), "r"(n) : "memory"); }
__device__ __forceinline__ void mbar_arrive_cl_release(uint32_t cl_addr) { asm volatile("mbarrier.arrive.release.cluster.shared::cluster.b64 _, [%0];" :: "r"(cl_addr) : "memory"); }
__device__ __forceinline__ void mbar_wait(uint32_t bar, uint32_t parity) {
    asm volatile("{\n.reg .pred p;\n.reg .u32 c;\nmov.u32 c, 0;\n"
                 "MW_LOOP:\nmbarrier.try_wait.parity.shared::cta.b64 p, [%0], %1;\n@p bra MW_DONE;\n"
                 "add.u32 c, c, 1;\nsetp.lt.u32 p, c, 3000000;\n@p bra MW_LOOP;\ntrap;\nMW_DONE:\n}" :: "r"(bar), "r"(parity) : "memory");
}
__device__ __forceinline__ void mbar_wait_cl(uint32_t bar, uint32_t parity) {
    asm volatile("{\n.reg .pred p;\n.reg .u32 c;\nmov.u32 c, 0;\n"
                 "MW_LOOP:\nmbarrier.try_wait.parity.acquire.cluster.shared::cta.b64 p, [%0], %1;\n@p bra MW_DONE;\n"
                 "add.u32 c, c, 1;\nsetp.lt.u32 p, c, 3000000;\n@p bra MW_LOOP;\ntrap;\nMW_DONE:\n}" :: "r"(bar), "r"(parity) : "memory");
}
__device__ __forceinline__ void tma_load(uint32_t dst, const CUtensorMap* map, int c0, int c1, uint32_t bar) {
    asm volatile("cp.async.bulk.tensor.2d.shared::cluster.global.mbarrier::complete_tx::bytes [%0], [%1, {%3, %4}], [%2];"
                 :: "r"(dst), "l"(map), "r"(bar), "r"(c0), "r"(c1) : "memory");
}
__device__ __forceinline__ void tma_load_mc(uint32_t dst, const CUtensorMap* map, int c0, int c1, uint32_t bar) {
    asm volatile("cp.async.bulk.tensor.2d.shared::cluster.global.mbarrier::complete_tx::bytes.multicast::cluster [%0], [%1, {%3, %4}], [%2], %5;"
                 :: "r"(dst), "l"(map), "r"(bar), "r"(c0), "r"(c1), "h"((uint16_t)3) : "memory");
}
__device__ __forceinline__ void tma_prefetch(const CUtensorMap* map, int c0, int c1) {
    asm volatile("cp.async.bulk.prefetch.tensor.2d.L2.global [%0, {%1, %2}];" :: "l"(map), "r"(c0), "r"(c1) : "memory");
}
__device__ __forceinline__ void prefetch_l2(const void* p) { asm volatile("prefetch.global.L2 [%0];" :: "l"(p)); }
__device__ __forceinline__ void bulk_prefetch(const void* p, uint32_t bytes) {
    asm volatile("cp.async.bulk.prefetch.L2.global [%0], %1;" :: "l"(p), "r"(bytes) : "memory");
}
__device__ __forceinline__ void tma_store(const CUtensorMap* map, uint32_t src, int c0, int c1) {
    asm volatile("cp.async.bulk.tensor.2d.global.shared::cta.bulk_group [%0, {%2, %3}], [%1];" :: "l"(map), "r"(src), "r"(c0), "r"(c1) : "memory");
}
__device__ __forceinline__ void bulk_commit() { asm volatile("cp.async.bulk.commit_group;" ::: "memory"); }
__device__ __forceinline__ void bulk_wait_all() { asm volatile("cp.async.bulk.wait_group 0;" ::: "memory"); }
__device__ __forceinline__ void fence_async_smem() { asm volatile("fence.proxy.async.shared::cta;" ::: "memory"); }
__device__ __forceinline__ void fence_async_global() { asm volatile("fence.proxy.async.global;" ::: "memory"); }
__device__ __forceinline__ bool elect_one() {
    uint32_t pred;
    asm volatile("{\n.reg .pred p;\nelect.sync _|p, 0xffffffff;\nselp.u32 %0, 1, 0, p;\n}" : "=r"(pred));
    return pred != 0;
}
__device__ __forceinline__ void cluster_arrive() { asm volatile("barrier.cluster.arrive.relaxed.aligned;" ::: "memory"); }
__device__ __forceinline__ void cluster_wait() { asm volatile("barrier.cluster.wait.aligned;" ::: "memory"); }
__device__ __forceinline__ void named_bar(int id, int n) { asm volatile("bar.sync %0, %1;" :: "r"(id), "r"(n) : "memory"); }
__device__ __forceinline__ void wgmma_fence() { asm volatile("wgmma.fence.sync.aligned;" ::: "memory"); }
__device__ __forceinline__ void wgmma_commit() { asm volatile("wgmma.commit_group.sync.aligned;" ::: "memory"); }
template <int N> __device__ __forceinline__ void wgmma_wait() { asm volatile("wgmma.wait_group.sync.aligned %0;" :: "n"(N) : "memory"); }
template <int R> __device__ __forceinline__ void reg_alloc() { asm volatile("setmaxnreg.inc.sync.aligned.u32 %0;" :: "n"(R)); }
template <int R> __device__ __forceinline__ void reg_dealloc() { asm volatile("setmaxnreg.dec.sync.aligned.u32 %0;" :: "n"(R)); }
__device__ __forceinline__ unsigned ld_acquire(const unsigned* p) { unsigned v; asm volatile("ld.acquire.gpu.global.u32 %0, [%1];" : "=r"(v) : "l"(p) : "memory"); return v; }
__device__ __forceinline__ unsigned ld_relaxed(const unsigned* p) { unsigned v; asm volatile("ld.relaxed.gpu.global.u32 %0, [%1];" : "=r"(v) : "l"(p) : "memory"); return v; }
__device__ __forceinline__ void st_relaxed(unsigned* p, unsigned v) { asm volatile("st.relaxed.gpu.global.u32 [%0], %1;" :: "l"(p), "r"(v) : "memory"); }
__device__ __forceinline__ void bulk_load(uint32_t dst, const void* g, uint32_t bytes, uint32_t bar) {
    asm volatile("cp.async.bulk.shared::cluster.global.mbarrier::complete_tx::bytes [%0], [%1], %2, [%3];" :: "r"(dst), "l"(g), "r"(bytes), "r"(bar) : "memory");
}
__device__ __forceinline__ void sts_u(uint32_t a, uint32_t v) { asm volatile("st.shared.u32 [%0], %1;" :: "r"(a), "r"(v) : "memory"); }
__device__ __forceinline__ uint32_t lds_u(uint32_t a) { uint32_t v; asm volatile("ld.shared.u32 %0, [%1];" : "=r"(v) : "r"(a)); return v; }
__device__ __forceinline__ void bulk_store(void* g, uint32_t src, uint32_t bytes) {
    asm volatile("cp.async.bulk.global.shared::cta.bulk_group [%0], [%1], %2;" :: "l"(g), "r"(src), "r"(bytes) : "memory");
}
__device__ __forceinline__ void sts_u4(uint32_t a, uint4 v) { asm volatile("st.shared.v4.u32 [%0], {%1, %2, %3, %4};" :: "r"(a), "r"(v.x), "r"(v.y), "r"(v.z), "r"(v.w) : "memory"); }
__device__ __forceinline__ void sts_f2(uint32_t a, float x, float y) { asm volatile("st.shared.v2.f32 [%0], {%1, %2};" :: "r"(a), "f"(x), "f"(y) : "memory"); }
__device__ __forceinline__ void st_release(unsigned* p, unsigned v) { asm volatile("st.release.gpu.global.u32 [%0], %1;" :: "l"(p), "r"(v) : "memory"); }
__device__ __forceinline__ uint4 ldg_stream(const void* p) {
    uint4 v; asm volatile("ld.global.nc.L1::no_allocate.v4.u32 {%0, %1, %2, %3}, [%4];" : "=r"(v.x), "=r"(v.y), "=r"(v.z), "=r"(v.w) : "l"(p)); return v;
}
__device__ __forceinline__ void ldg_stream_inplace(uint4& v, const void* p) {
    asm volatile("ld.global.nc.L1::no_allocate.v4.u32 {%0, %1, %2, %3}, [%4];" : "+r"(v.x), "+r"(v.y), "+r"(v.z), "+r"(v.w) : "l"(p));
}
__device__ __forceinline__ uint64_t make_desc(uint32_t addr, uint32_t lbo, uint32_t sbo) {
    return (uint64_t)((addr & 0x3FFFF) >> 4) | ((uint64_t)(lbo >> 4) << 16) | ((uint64_t)(sbo >> 4) << 32) | ((uint64_t)1 << 62);
}
__device__ __forceinline__ uint32_t pack_bf16(float lo, float hi) {
    uint32_t r; asm("cvt.rn.bf16x2.f32 %0, %1, %2;" : "=r"(r) : "f"(hi), "f"(lo)); return r;
}
__device__ __forceinline__ float bf_lo(uint32_t v) { return __uint_as_float(v << 16); }
__device__ __forceinline__ float bf_hi(uint32_t v) { return __uint_as_float(v & 0xffff0000u); }
__device__ __forceinline__ float bf_round(float v) { return __bfloat162float(__float2bfloat16_rn(v)); }
__device__ __forceinline__ void stsm4(uint32_t addr, uint32_t r0, uint32_t r1, uint32_t r2, uint32_t r3) {
    asm volatile("stmatrix.sync.aligned.m8n8.x4.shared.b16 [%0], {%1, %2, %3, %4};" :: "r"(addr), "r"(r0), "r"(r1), "r"(r2), "r"(r3) : "memory");
}
__device__ __forceinline__ void ldsm4(uint32_t addr, uint32_t& r0, uint32_t& r1, uint32_t& r2, uint32_t& r3) {
    asm volatile("ldmatrix.sync.aligned.m8n8.x4.shared.b16 {%0, %1, %2, %3}, [%4];" : "=r"(r0), "=r"(r1), "=r"(r2), "=r"(r3) : "r"(addr) : "memory");
}
__device__ __forceinline__ void mma_rowsum(float (&c)[4], uint32_t a0, uint32_t a1, uint32_t a2, uint32_t a3) {
    asm volatile("mma.sync.aligned.m16n8k16.row.col.f32.bf16.bf16.f32 {%0, %1, %2, %3}, {%4, %5, %6, %7}, {%8, %8}, {%0, %1, %2, %3};"
                 : "+f"(c[0]), "+f"(c[1]), "+f"(c[2]), "+f"(c[3]) : "r"(a0), "r"(a1), "r"(a2), "r"(a3), "r"(0x3f803f80u));
}
__device__ __forceinline__ float lds_f(uint32_t a) { float v; asm volatile("ld.shared.f32 %0, [%1];" : "=f"(v) : "r"(a)); return v; }
__device__ __forceinline__ float2 lds_f2(uint32_t a) { float2 v; asm volatile("ld.shared.v2.f32 {%0, %1}, [%2];" : "=f"(v.x), "=f"(v.y) : "r"(a)); return v; }
__device__ __forceinline__ float4 lds_f4(uint32_t a) { float4 v; asm volatile("ld.shared.v4.f32 {%0, %1, %2, %3}, [%4];" : "=f"(v.x), "=f"(v.y), "=f"(v.z), "=f"(v.w) : "r"(a)); return v; }
__device__ __forceinline__ uint4 lds_u4(uint32_t a) { uint4 v; asm volatile("ld.shared.v4.u32 {%0, %1, %2, %3}, [%4];" : "=r"(v.x), "=r"(v.y), "=r"(v.z), "=r"(v.w) : "r"(a)); return v; }
__device__ __forceinline__ void sts_f(uint32_t a, float v) { asm volatile("st.shared.f32 [%0], %1;" :: "r"(a), "f"(v) : "memory"); }
__device__ __forceinline__ void st_cluster_f(uint32_t cl_addr, float v) { asm volatile("st.shared::cluster.f32 [%0], %1;" :: "r"(cl_addr), "f"(v) : "memory"); }
__device__ __forceinline__ void st_async4(uint32_t cl_addr, float a, float b, float c, float d, uint32_t cl_bar) {
    asm volatile("st.async.weak.shared::cluster.mbarrier::complete_tx::bytes.v4.f32 [%0], {%1, %2, %3, %4}, [%5];"
                 :: "r"(cl_addr), "f"(a), "f"(b), "f"(c), "f"(d), "r"(cl_bar) : "memory");
}
__device__ __forceinline__ float tanh_fast(float x) { float y; asm("tanh.approx.f32 %0, %1;" : "=f"(y) : "f"(x)); return y; }
template <int N> __device__ __forceinline__ void fence_regs(float (&a)[N]) {
#pragma unroll
    for (int i = 0; i < N; i++) asm volatile("" : "+f"(a[i]) :: "memory");
}
__device__ __forceinline__ void cnt_add(int idx) { asm volatile("red.relaxed.gpu.global.add.u32 [%0], 1;" :: "l"(g_cnt + idx * 32) : "memory"); }
template <int SLEEP_NS>
__device__ __forceinline__ void cnt_wait(int idx, unsigned tag, unsigned per) {
    const unsigned target = tag * per;
    const unsigned* c = g_cnt + idx * 32;
    unsigned it = 0;
    while ((int)(ld_relaxed(c) - target) < 0) {
        if (SLEEP_NS > 0) __nanosleep(SLEEP_NS);
        if (++it > 4000000u) __trap();
    }
    asm volatile("fence.acquire.gpu;" ::: "memory");
}

template <int TB>
__device__ __forceinline__ void wgmma_n128(float (&d)[64], uint64_t da, uint64_t db, int scale_d) {
    asm volatile("{\n.reg .pred p;\nsetp.ne.b32 p, %66, 0;\n"
        "wgmma.mma_async.sync.aligned.m64n128k16.f32.bf16.bf16 {"
        "%0, %1, %2, %3, %4, %5, %6, %7, %8, %9, %10, %11, %12, %13, %14, %15, "
        "%16, %17, %18, %19, %20, %21, %22, %23, %24, %25, %26, %27, %28, %29, %30, %31, "
        "%32, %33, %34, %35, %36, %37, %38, %39, %40, %41, %42, %43, %44, %45, %46, %47, "
        "%48, %49, %50, %51, %52, %53, %54, %55, %56, %57, %58, %59, %60, %61, %62, %63}, "
        "%64, %65, p, 1, 1, 0, %67;\n}"
        : "+f"(d[0]), "+f"(d[1]), "+f"(d[2]), "+f"(d[3]), "+f"(d[4]), "+f"(d[5]), "+f"(d[6]), "+f"(d[7]),
          "+f"(d[8]), "+f"(d[9]), "+f"(d[10]), "+f"(d[11]), "+f"(d[12]), "+f"(d[13]), "+f"(d[14]), "+f"(d[15]),
          "+f"(d[16]), "+f"(d[17]), "+f"(d[18]), "+f"(d[19]), "+f"(d[20]), "+f"(d[21]), "+f"(d[22]), "+f"(d[23]),
          "+f"(d[24]), "+f"(d[25]), "+f"(d[26]), "+f"(d[27]), "+f"(d[28]), "+f"(d[29]), "+f"(d[30]), "+f"(d[31]),
          "+f"(d[32]), "+f"(d[33]), "+f"(d[34]), "+f"(d[35]), "+f"(d[36]), "+f"(d[37]), "+f"(d[38]), "+f"(d[39]),
          "+f"(d[40]), "+f"(d[41]), "+f"(d[42]), "+f"(d[43]), "+f"(d[44]), "+f"(d[45]), "+f"(d[46]), "+f"(d[47]),
          "+f"(d[48]), "+f"(d[49]), "+f"(d[50]), "+f"(d[51]), "+f"(d[52]), "+f"(d[53]), "+f"(d[54]), "+f"(d[55]),
          "+f"(d[56]), "+f"(d[57]), "+f"(d[58]), "+f"(d[59]), "+f"(d[60]), "+f"(d[61]), "+f"(d[62]), "+f"(d[63])
        : "l"(da), "l"(db), "r"(scale_d), "n"(TB));
}
template <int TB>
__device__ __forceinline__ void wgmma_n176(float (&d)[88], uint64_t da, uint64_t db, int scale_d) {
    asm volatile("{\n.reg .pred p;\nsetp.ne.b32 p, %90, 0;\n"
        "wgmma.mma_async.sync.aligned.m64n176k16.f32.bf16.bf16 {"
        "%0, %1, %2, %3, %4, %5, %6, %7, %8, %9, %10, %11, %12, %13, %14, %15, "
        "%16, %17, %18, %19, %20, %21, %22, %23, %24, %25, %26, %27, %28, %29, %30, %31, "
        "%32, %33, %34, %35, %36, %37, %38, %39, %40, %41, %42, %43, %44, %45, %46, %47, "
        "%48, %49, %50, %51, %52, %53, %54, %55, %56, %57, %58, %59, %60, %61, %62, %63, "
        "%64, %65, %66, %67, %68, %69, %70, %71, %72, %73, %74, %75, %76, %77, %78, %79, "
        "%80, %81, %82, %83, %84, %85, %86, %87}, "
        "%88, %89, p, 1, 1, 0, %91;\n}"
        : "+f"(d[0]), "+f"(d[1]), "+f"(d[2]), "+f"(d[3]), "+f"(d[4]), "+f"(d[5]), "+f"(d[6]), "+f"(d[7]),
          "+f"(d[8]), "+f"(d[9]), "+f"(d[10]), "+f"(d[11]), "+f"(d[12]), "+f"(d[13]), "+f"(d[14]), "+f"(d[15]),
          "+f"(d[16]), "+f"(d[17]), "+f"(d[18]), "+f"(d[19]), "+f"(d[20]), "+f"(d[21]), "+f"(d[22]), "+f"(d[23]),
          "+f"(d[24]), "+f"(d[25]), "+f"(d[26]), "+f"(d[27]), "+f"(d[28]), "+f"(d[29]), "+f"(d[30]), "+f"(d[31]),
          "+f"(d[32]), "+f"(d[33]), "+f"(d[34]), "+f"(d[35]), "+f"(d[36]), "+f"(d[37]), "+f"(d[38]), "+f"(d[39]),
          "+f"(d[40]), "+f"(d[41]), "+f"(d[42]), "+f"(d[43]), "+f"(d[44]), "+f"(d[45]), "+f"(d[46]), "+f"(d[47]),
          "+f"(d[48]), "+f"(d[49]), "+f"(d[50]), "+f"(d[51]), "+f"(d[52]), "+f"(d[53]), "+f"(d[54]), "+f"(d[55]),
          "+f"(d[56]), "+f"(d[57]), "+f"(d[58]), "+f"(d[59]), "+f"(d[60]), "+f"(d[61]), "+f"(d[62]), "+f"(d[63]),
          "+f"(d[64]), "+f"(d[65]), "+f"(d[66]), "+f"(d[67]), "+f"(d[68]), "+f"(d[69]), "+f"(d[70]), "+f"(d[71]),
          "+f"(d[72]), "+f"(d[73]), "+f"(d[74]), "+f"(d[75]), "+f"(d[76]), "+f"(d[77]), "+f"(d[78]), "+f"(d[79]),
          "+f"(d[80]), "+f"(d[81]), "+f"(d[82]), "+f"(d[83]), "+f"(d[84]), "+f"(d[85]), "+f"(d[86]), "+f"(d[87])
        : "l"(da), "l"(db), "r"(scale_d), "n"(TB));
}
template <int TB>
__device__ __forceinline__ void wgmma_n8(float (&d)[4], uint64_t da, uint64_t db, int scale_d) {
    asm volatile("{\n.reg .pred p;\nsetp.ne.b32 p, %6, 0;\n"
        "wgmma.mma_async.sync.aligned.m64n8k16.f32.bf16.bf16 {"
        "%0, %1, %2, %3}, "
        "%4, %5, p, 1, 1, 0, %7;\n}"
        : "+f"(d[0]), "+f"(d[1]), "+f"(d[2]), "+f"(d[3])
        : "l"(da), "l"(db), "r"(scale_d), "n"(TB));
}

template <bool B> struct BoolC { static constexpr bool value = B; };
__device__ __forceinline__ uint32_t bit(uint32_t mask, int i) { return (mask >> i) & 1u; }
__device__ __forceinline__ uint32_t a_slot_addr(uint32_t sb, int w, int slot) {
    return slot < NA ? sb + OFF_A + w * (NA * 8192) + slot * 8192 : sb + OFF_B + (7 + w) * 16384 + (slot - NA) * 8192;
}

__global__ void __launch_bounds__(384, 1) mega_kernel(const __grid_constant__ Params p) {
    extern __shared__ __align__(1024) uint8_t smem_raw[];
    TRACE_INIT();
    const int tid = threadIdx.x;
    const int b = blockIdx.x;
    const int lane = tid & 31;
    uint4 xv[2][2];
    if (tid >= 128) {
        const __nv_bfloat16* xr = p.x + (size_t)(b * 16 + ((tid - 128) >> 5) * 2) * D_ + lane * 8;
#pragma unroll
        for (int rr = 0; rr < 2; rr++) { xv[rr][0] = ldg_stream(xr + rr * D_); xv[rr][1] = ldg_stream(xr + rr * D_ + 256); }
    }
    const unsigned tag = ld_relaxed(&g_epoch) + 1;
    const uint32_t sb = smem_u32(smem_raw);
    if (sb & 1023u) __trap();
    const int warp = __shfl_sync(0xffffffffu, tid >> 5, 0);
    const int rho = b & 1;
    const int pc = b >> 1;
    const int mt1 = pc >> 1, part1 = mt1 >> 4, i1 = mt1 & 15, nt1 = (pc & 1) * 2 + rho;
    const int i2 = pc >> 2, q2 = pc & 3;
    const int i3 = (pc >> 3) * 2 + rho, j3 = pc & 7;

    if (tid == 0) TRACE_GT(0);
    {
        constexpr int NBAR = (SMEM_USED - OFF_BAR) / 8;
        if (elect_one()) {
#pragma unroll 1
            for (int i = warp; i < NBAR; i += 12) {
                uint32_t a = OFF_BAR + 8 * i;
                uint32_t cnt = 1;
                if (a >= BAR_EMPTYB && a < BAR_FULLA) cnt = 2;
                else if (a == BAR_XARR) cnt = 8;
                mbar_init(sb + a, cnt);
            }
            asm volatile("fence.mbarrier_init.release.cluster;" ::: "memory");
        }
    }
    if (warp == 3) {
#pragma unroll
        for (int k = 0; k < 2; k++) asm volatile("st.shared.v4.u32 [%0], {%1, %1, %1, %1};" :: "r"(sb + OFF_ONES + (lane + 32 * k) * 16), "r"(0x3f803f80u) : "memory");
        fence_async_smem();
    }
    const uint32_t peer_sb = mapa(sb, rho ^ 1);
    __syncthreads();
    cluster_arrive();

    if (warp < 4) {
        cluster_wait();
        if (tid == 0) TRACE(33);
        reg_dealloc<72>();
        if (warp == 0) {
            if (elect_one()) {
                cnt_wait<0>(CN_X + (pc & 7), tag, 128);
                fence_async_global();
                uint32_t ph = 0x1ff;
                TRACE(1);
                int slot = 0;
#pragma unroll 1
                for (int kb = 0; kb < 32; kb++) {
                    uint32_t full = sb + BAR_FULLB + 8 * slot, dst = sb + OFF_B + slot * 16384;
                    mbar_wait(sb + BAR_EMPTYB + 8 * slot, bit(ph, slot));
                    TRACE2(6, kb);
                    mbar_expect_tx(full, 16384);
                    tma_load(dst, &p.m[M_XN], nt1 * 128, kb * 64, full);
                    tma_load(dst + 8192, &p.m[M_XN], nt1 * 128 + 64, kb * 64, full);
                    if (kb == 12) { bulk_prefetch((const char*)p.dr + (size_t)b * 4096, 4096); bulk_prefetch((const char*)p.di + (size_t)b * 4096, 4096); }
                    if (kb == 16) bulk_prefetch((const char*)p.wg + (size_t)b * 11008, 11008);
                    if (kb == 20) bulk_prefetch((const char*)p.wu + (size_t)b * 11008, 11008);
                    if (kb == 26) bulk_prefetch((const char*)p.wd + (size_t)b * 11008, 11008);
                    ph ^= 1u << slot;
                    if (++slot == NB1) slot = 0;
                }
                const CUtensorMap* md = &p.m[rho ? M_DI : M_DR];
#pragma unroll 1
                for (int kb = 0; kb < 8; kb++) {
                    slot = (P2_SLOTS >> (4 * kb)) & 15;
                    uint32_t full = sb + BAR_FULLB + 8 * slot, dst = sb + OFF_B + slot * 16384;
                    if (slot >= 7) {
                        mbar_wait(sb + BAR_EMPTYA + 8 * (NA1 * (slot - 7) + 4), 0);
                        mbar_wait(sb + BAR_EMPTYA + 8 * (NA1 * (slot - 7) + 5), 0);
                    } else {
                        mbar_wait(sb + BAR_EMPTYB + 8 * slot, bit(ph, slot));
                    }
                    mbar_expect_tx(full, 16384);
                    tma_load(dst, md, kb * 64, q2 * 128 + rho * 64, full);
                    tma_load(dst + 8192, md, kb * 64, q2 * 128 + (rho ^ 1) * 64, full);
                    ph ^= 1u << slot;
                }
                const CUtensorMap* mw = &p.m[rho ? M_WU : M_WG];
                slot = 3;
#pragma unroll 1
                for (int kb = 0; kb < 8; kb++) {
                    uint32_t dst = sb + OFF_B + slot * 16384;
                    uint32_t full = sb + BAR_FULLB + 8 * slot;
                    mbar_wait(sb + BAR_EMPTYB + 8 * slot, bit(ph, slot));
                    if (kb < 3) {
                        mbar_wait(sb + BAR_EMPTYB + 8 * (slot + 1), bit(ph, slot + 1)); mbar_wait(sb + BAR_EMPTYB + 8 * (slot + 2), bit(ph, slot + 2));
                        mbar_wait(sb + BAR_PEMPTYB + 8 * (slot + 1), 0); mbar_wait(sb + BAR_PEMPTYB + 8 * (slot + 2), 0);
                    }
                    mbar_expect_tx(full, 49152);
                    mbar_wait(sb + BAR_PEMPTYB + 8 * slot, (kb / 3) & 1);
                    TRACE2(5, 8 + kb);
#pragma unroll
                    for (int ch = 0; ch < 3; ch++) tma_load_mc(dst + (rho * 3 + ch) * 8192, mw, j3 * 176 + ch * 64, kb * 64, full);
                    ph ^= 1u << slot;
                    slot += 3; if (slot == NB) slot = 0;
                }
                slot = 0;
                const uint32_t ph0 = ph;
#pragma unroll 1
                for (int kb = 0; kb < NKB4; kb++) {
                    uint32_t full = sb + BAR_FULLB + 8 * slot, dst = sb + OFF_B + slot * 16384;
                    if (kb < NB && slot % 3 != 0) { const int g0 = slot - slot % 3; mbar_wait(sb + BAR_EMPTYB + 8 * g0, bit(ph0, g0)); }
                    else mbar_wait(sb + BAR_EMPTYB + 8 * slot, bit(ph, slot));
                    mbar_expect_tx(full, 16384);
                    tma_load(dst, &p.m[M_WD], q2 * 128 + rho * 64, rho * 704 + kb * 64, full);
                    tma_load(dst + 8192, &p.m[M_WD], q2 * 128 + (rho ^ 1) * 64, rho * 704 + kb * 64, full);
                    ph ^= 1u << slot;
                    if (++slot == NB) slot = 0;
                }
            }
        } else if (warp <= 2) {
            const int w = warp - 1;
            const uint32_t fullb = sb + BAR_FULLA + 8 * NA1 * w, emptyb = sb + BAR_EMPTYA + 8 * NA1 * w;
            const uint32_t pemptyb = sb + BAR_PEMPTYA + 8 * NA1 * w;
            uint32_t ph = 0x3f;
            if (elect_one()) {
                const CUtensorMap* ma = &p.m[part1 ? M_WIM : M_WRE];
                const int row0 = i1 * 128 + w * 64;
                int slot = 0, lap = 0;
                mbar_wait(sb + BAR_XARR, 0);
#pragma unroll 1
                for (int m = 0; m < 32; m++) {
                    mbar_wait(emptyb + 8 * slot, bit(ph, slot));
                    mbar_expect_tx(fullb + 8 * slot, 8192);
                    if ((m & 1) == rho) {
                        if (lap > 0) mbar_wait(pemptyb + 8 * slot, (lap - 1) & 1);
                        tma_load_mc(a_slot_addr(sb, w, slot), ma, m * 64, row0, fullb + 8 * slot);
                    }
                    if (w == 0) TRACE2(3, m);
                    ph ^= 1u << slot;
                    if (++slot == NA1) { slot = 0; lap++; }
                }
#pragma unroll 1
                for (int phs = 0; phs < 3; phs++) {
                    const int cidx = phs == 0 ? CN_1 + (rho * 16 + i2) * 2 + w : (phs == 1 ? CN_2 + i3 * 2 + w : CN_3 + (i2 * 2 + rho) * 2 + w);
                    const CUtensorMap* mp = &p.m[phs == 0 ? M_PQ : (phs == 1 ? M_Z : M_HLD)];
                    const int col0 = phs == 0 ? rho * 512 : (phs == 1 ? 0 : rho * 704), row0 = (phs == 1 ? i3 : i2) * 128 + w * 64;
                    const int nkb = phs == 2 ? NKB4 : 8;
                    cnt_wait<0>(cidx, tag, phs == 1 ? 8 : 4);
                    fence_async_global();
#pragma unroll 1
                    for (int kb = 0; kb < nkb; kb++) {
                        int sl = kb & 3;
                        mbar_wait(emptyb + 8 * sl, bit(ph, sl));
                        mbar_expect_tx(fullb + 8 * sl, 8192);
                        tma_load(a_slot_addr(sb, w, sl), mp, col0 + kb * 64, row0, fullb + 8 * sl);
                        ph ^= 1u << sl;
                    }
                    if (w == 0) TRACE(2 + phs);
                }
            }
        } else {
            mbar_wait(sb + BAR_XARR, 0);
            {
#pragma unroll
                for (int k = 0; k < 2; k++) {
                    const uint4 cv = ldg_stream(p.c + (lane + 32 * k) * 8);
                    const uint32_t cu[4] = {cv.x, cv.y, cv.z, cv.w};
#pragma unroll
                    for (int e = 0; e < 8; e++) {
                        const float cval = (e & 1) ? bf_hi(cu[e >> 1]) : bf_lo(cu[e >> 1]);
                        sts_f(sb + OFF_RED + ((lane + 32 * k) * 8 + e) * 4, bf_round(__fdividef(cval, 1.f + __expf(-cval))));
                    }
                }
                __syncwarp();
            }
            {
                const int cg = lane & 3, rg = lane >> 2;
                float a8[8];
#pragma unroll
                for (int e = 0; e < 8; e++) a8[e] = 0.f;
                if (b < 96) {
                    if (elect_one()) {
#pragma unroll
                        for (int c = 0; c < 2; c++) { mbar_expect_tx(sb + BAR_WM + 8 * c, 4096); tma_load(sb + OFF_WM + c * 4096, &p.m[M_WMOD], b * 32, c * 64, sb + BAR_WM + 8 * c); }
                    }
                    __syncwarp();
#pragma unroll 1
                    for (int c = 0; c < 8; c++) {
                        mbar_wait(sb + BAR_WM + 8 * (c & 1), (c >> 1) & 1);
                        uint4 v[8];
#pragma unroll
                        for (int i = 0; i < 8; i++) v[i] = lds_u4(sb + OFF_WM + (c & 1) * 4096 + (i * 8 + rg) * 64 + cg * 16);
                        float sl[8];
#pragma unroll
                        for (int i = 0; i < 8; i++) sl[i] = lds_f(sb + OFF_RED + (c * 64 + i * 8 + rg) * 4);
#pragma unroll
                        for (int i = 0; i < 8; i++) {
                            const float f[8] = {bf_lo(v[i].x), bf_hi(v[i].x), bf_lo(v[i].y), bf_hi(v[i].y), bf_lo(v[i].z), bf_hi(v[i].z), bf_lo(v[i].w), bf_hi(v[i].w)};
#pragma unroll
                            for (int e = 0; e < 8; e++) a8[e] = fmaf(sl[i], f[e], a8[e]);
                        }
                        __syncwarp();
                        if (c + 2 < 8 && elect_one()) {
                            mbar_expect_tx(sb + BAR_WM + 8 * (c & 1), 4096);
                            tma_load(sb + OFF_WM + (c & 1) * 4096, &p.m[M_WMOD], b * 32, (c + 2) * 64, sb + BAR_WM + 8 * (c & 1));
                        }
                        __syncwarp();
                    }
                }
                if (b < 96) {
#pragma unroll
                    for (int e = 0; e < 8; e++) {
#pragma unroll
                        for (int o = 4; o < 32; o <<= 1) a8[e] += __shfl_xor_sync(0xffffffffu, a8[e], o);
                    }
                    if (rg == 0) {
#pragma unroll
                        for (int e = 0; e < 8; e++) sts_f(sb + OFF_PUB + (cg * 8 + e) * 4, bf_round(a8[e]));
                    }
                    fence_async_smem();
                    __syncwarp();
                    if (elect_one()) {
                        bulk_store(g_mod + b * 32, sb + OFF_PUB, 128);
                        bulk_commit();
                        bulk_wait_all();
                        cnt_add(CN_MOD); cnt_add(CN_MOD + 1);
                        TRACE(51);
                    }
                    __syncwarp();
                }
            }
            uint32_t wmph = (b < 96) ? 0u : 0u;
            if (elect_one()) {
                const __nv_bfloat16* D = (b < 64 ? p.dr : p.di) + (size_t)((b & 63) * 8) * D_;
#pragma unroll
                for (int c = 0; c < 2; c++) { mbar_expect_tx(sb + BAR_WM + 8 * c, 4096); bulk_load(sb + OFF_WM + c * 4096, D + c * 4 * D_, 4096, sb + BAR_WM + 8 * c); }
            }
            __syncwarp();
            if (lane == 0) cnt_wait<200>(CN_MOD + (b & 1), tag, 96);
            __syncwarp();
            {
                const float* md = g_mod;
                float t0[4], t1[6];
                float4 sa4[4];
#pragma unroll
                for (int k = 0; k < 4; k++) t0[k] = __ldcg(md + 1 * 512 + nt1 * 128 + lane + 32 * k);
#pragma unroll
                for (int k = 0; k < 2; k++) {
                    const int col = q2 * 128 + rho * 64 + lane + 32 * k;
                    t1[3 * k] = __ldcg(md + 2 * 512 + col); t1[3 * k + 1] = __ldcg(md + 4 * 512 + col); t1[3 * k + 2] = __ldcg(md + 5 * 512 + col);
                }
#pragma unroll
                for (int k = 0; k < 4; k++) sa4[k] = __ldcg((const float4*)(md + (k >> 1) * 256 + lane * 8 + (k & 1) * 4));
#pragma unroll
                for (int k = 0; k < 4; k++) sts_f(sb + OFF_CA1 + (lane + 32 * k) * 4, bf_round(1.f + t0[k]));
#pragma unroll
                for (int k = 0; k < 2; k++) {
                    sts_f(sb + OFF_GA + (lane + 32 * k) * 4, t1[3 * k]); sts_f(sb + OFF_CB1 + (lane + 32 * k) * 4, bf_round(1.f + t1[3 * k + 1])); sts_f(sb + OFF_GB + (lane + 32 * k) * 4, t1[3 * k + 2]);
                }
                __syncwarp();
                if (lane == 0) { mbar_arrive(sb + BAR_AUX); TRACE(52); }
#pragma unroll
                for (int c = 0; c < 2; c++) {
                    mbar_wait(sb + BAR_WM + 8 * c, wmph);
#pragma unroll
                    for (int r = 0; r < 4; r++) {
                        const uint4 d0 = lds_u4(sb + OFF_WM + c * 4096 + r * 1024 + lane * 16), d1 = lds_u4(sb + OFF_WM + c * 4096 + r * 1024 + 512 + lane * 16);
                        const uint32_t u[8] = {d0.x, d0.y, d0.z, d0.w, d1.x, d1.y, d1.z, d1.w};
                        float a = 0.f;
#pragma unroll
                        for (int hh = 0; hh < 2; hh++) {
                            const float4 s0 = sa4[hh * 2], s1 = sa4[hh * 2 + 1];
                            a = fmaf(s0.x, bf_lo(u[hh * 4]), fmaf(s0.y, bf_hi(u[hh * 4]), a)); a = fmaf(s0.z, bf_lo(u[hh * 4 + 1]), fmaf(s0.w, bf_hi(u[hh * 4 + 1]), a));
                            a = fmaf(s1.x, bf_lo(u[hh * 4 + 2]), fmaf(s1.y, bf_hi(u[hh * 4 + 2]), a)); a = fmaf(s1.z, bf_lo(u[hh * 4 + 3]), fmaf(s1.w, bf_hi(u[hh * 4 + 3]), a));
                        }
#pragma unroll
                        for (int o = 16; o > 0; o >>= 1) a += __shfl_xor_sync(0xffffffffu, a, o);
                        if (lane == 0) sts_f(sb + OFF_PUB + 384 + (c * 4 + r) * 4, a);
                    }
                }
                wmph ^= 1;
                fence_async_smem();
                __syncwarp();
                if (elect_one()) {
                    bulk_store(g_v + b * 8, sb + OFF_PUB + 384, 32);
                    bulk_commit();
                    bulk_wait_all();
                    cnt_add(CN_V); cnt_add(CN_V + 1);
                }
                __syncwarp();
            }
            const int isu = b >= 43, col0 = (b - isu * 43) * 32;
            const CUtensorMap* mcs = &p.m[isu ? M_WU32 : M_WG32];
            auto load_v_slices = [&]() {
                if (lane == 0) cnt_wait<200>(CN_V + (b & 1), tag, 128);
                __syncwarp();
                const float sg = rho ? -1.f : 1.f;
                float t[4];
#pragma unroll
                for (int k = 0; k < 4; k++) { const int cidx = lane + 32 * k; t[k] = __ldcg(g_v + rho * 512 + q2 * 128 + ((cidx >> 6) ^ rho) * 64 + (cidx & 63)); }
#pragma unroll
                for (int k = 0; k < 4; k++) sts_f(sb + OFF_SA + (lane + 32 * k) * 4, sg * t[k]);
                __syncwarp();
                if (lane == 0) { mbar_arrive(sb + BAR_AUX + 8); TRACE(53); }
            };
            if (b < 86) {
                if (elect_one()) {
#pragma unroll
                    for (int c = 0; c < 2; c++) { mbar_expect_tx(sb + BAR_WM + 8 * c, 4096); tma_load(sb + OFF_WM + c * 4096, mcs, col0, c * 64, sb + BAR_WM + 8 * c); }
                }
                {
                    float tc[16], ts[16];
#pragma unroll
                    for (int k = 0; k < 16; k++) { tc[k] = __ldcg(g_mod + 4 * 512 + lane + 32 * k); ts[k] = __ldcg(g_mod + 3 * 512 + lane + 32 * k); }
#pragma unroll
                    for (int k = 0; k < 16; k++) sts_u(sb + OFF_RED + (lane + 32 * k) * 4, pack_bf16(1.f + tc[k], ts[k]));
                }
                __syncwarp();
                const int cg = lane & 3, rg = lane >> 2;
                float cs[8], bi[8];
#pragma unroll
                for (int e = 0; e < 8; e++) { cs[e] = 0.f; bi[e] = 0.f; }
#pragma unroll 1
                for (int c = 0; c < 8; c++) {
                    if (c == 2) load_v_slices();
                    mbar_wait(sb + BAR_WM + 8 * (c & 1), (wmph ^ (c >> 1)) & 1);
                    uint4 v[8]; uint32_t m[8];
#pragma unroll
                    for (int i = 0; i < 8; i++) v[i] = lds_u4(sb + OFF_WM + (c & 1) * 4096 + (i * 8 + rg) * 64 + cg * 16);
#pragma unroll
                    for (int i = 0; i < 8; i++) m[i] = lds_u(sb + OFF_RED + (c * 64 + i * 8 + rg) * 4);
#pragma unroll
                    for (int i = 0; i < 8; i++) {
                        const float f[8] = {bf_lo(v[i].x), bf_hi(v[i].x), bf_lo(v[i].y), bf_hi(v[i].y), bf_lo(v[i].z), bf_hi(v[i].z), bf_lo(v[i].w), bf_hi(v[i].w)};
                        const float m1 = bf_lo(m[i]), m0 = bf_hi(m[i]);
#pragma unroll
                        for (int e = 0; e < 8; e++) { cs[e] = fmaf(m1, f[e], cs[e]); bi[e] = fmaf(m0, f[e], bi[e]); }
                    }
                    __syncwarp();
                    if (c + 2 < 8 && elect_one()) {
                        mbar_expect_tx(sb + BAR_WM + 8 * (c & 1), 4096);
                        tma_load(sb + OFF_WM + (c & 1) * 4096, mcs, col0, (c + 2) * 64, sb + BAR_WM + 8 * (c & 1));
                    }
                    __syncwarp();
                }
#pragma unroll
                for (int e = 0; e < 8; e++) {
#pragma unroll
                    for (int o = 4; o < 32; o <<= 1) { cs[e] += __shfl_xor_sync(0xffffffffu, cs[e], o); bi[e] += __shfl_xor_sync(0xffffffffu, bi[e], o); }
                }
                if (rg == 0) {
#pragma unroll
                    for (int e = 0; e < 8; e++) { sts_f(sb + OFF_PUB + 128 + (cg * 8 + e) * 4, cs[e]); sts_f(sb + OFF_PUB + 256 + (cg * 8 + e) * 4, bi[e]); }
                }
                fence_async_smem();
                __syncwarp();
                if (elect_one()) {
                    bulk_store(g_cs + (isu * 2 + 0) * F_ + col0, sb + OFF_PUB + 128, 128);
                    bulk_store(g_cs + (isu * 2 + 1) * F_ + col0, sb + OFF_PUB + 256, 128);
                    bulk_commit();
                    bulk_wait_all();
                    cnt_add(CN_CS); cnt_add(CN_CS + 1);
                    TRACE(54);
                }
                __syncwarp();
            } else {
                load_v_slices();
            }
            if (lane == 0) cnt_wait<300>(CN_CS + (b & 1), tag, 86);
            __syncwarp();
            {
                float t[6][4];
#pragma unroll
                for (int k = 0; k < 6; k++) {
                    const int cidx = lane + 32 * k, f = j3 * 176 + cidx;
                    const bool ok = cidx < 176 && f < F_;
#pragma unroll
                    for (int q = 0; q < 4; q++) t[k][q] = ok ? __ldcg(g_cs + q * F_ + f) : 0.f;
                }
#pragma unroll
                for (int k = 0; k < 6; k++) {
                    const int cidx = lane + 32 * k;
                    if (cidx < 176) {
                        const uint32_t o = sb + OFF_T3 + (cidx >> 1) * 32 + (cidx & 1) * 4;
                        sts_f(o, t[k][0]); sts_f(o + 8, 0.5f * t[k][1]); sts_f(o + 16, t[k][2]); sts_f(o + 24, t[k][3]);
                    }
                }
            }
            __syncwarp();
            if (lane == 0) { mbar_arrive(sb + BAR_AUX + 16); TRACE(50); }
        }
        __syncwarp();
        cluster_arrive();
        cluster_wait();
    } else {
        const int ct = tid - 128;
        const int w = (warp >> 2) - 1;
        const int wt = ct & 127;
        const int cw = warp - 4;
        {
            float f[2][16];
#pragma unroll
            for (int rr = 0; rr < 2; rr++) {
                const uint32_t u[8] = {xv[rr][0].x, xv[rr][0].y, xv[rr][0].z, xv[rr][0].w, xv[rr][1].x, xv[rr][1].y, xv[rr][1].z, xv[rr][1].w};
#pragma unroll
                for (int k = 0; k < 8; k++) { f[rr][2 * k] = bf_lo(u[k]); f[rr][2 * k + 1] = bf_hi(u[k]); }
            }
            float s0 = 0.f, s1 = 0.f;
#pragma unroll
            for (int k = 0; k < 16; k++) { s0 += f[0][k]; s1 += f[1][k]; }
#pragma unroll
            for (int o = 16; o > 0; o >>= 1) { s0 += __shfl_xor_sync(0xffffffffu, s0, o); s1 += __shfl_xor_sync(0xffffffffu, s1, o); }
            if (ct == 0) TRACE(24);
            if (lane == 0) mbar_arrive(sb + BAR_XARR);
            s0 *= (1.f / 512.f); s1 *= (1.f / 512.f);
            float v0 = 0.f, v1 = 0.f;
#pragma unroll
            for (int k = 0; k < 16; k++) { f[0][k] -= s0; v0 = fmaf(f[0][k], f[0][k], v0); f[1][k] -= s1; v1 = fmaf(f[1][k], f[1][k], v1); }
#pragma unroll
            for (int o = 16; o > 0; o >>= 1) { v0 += __shfl_xor_sync(0xffffffffu, v0, o); v1 += __shfl_xor_sync(0xffffffffu, v1, o); }
            const float rstd[2] = {rsqrtf(v0 * (1.f / 512.f) + 1e-5f), rsqrtf(v1 * (1.f / 512.f) + 1e-5f)};
            const uint32_t stg = sb + OFF_B + cw * 2048 + lane * 16;
#pragma unroll
            for (int rr = 0; rr < 2; rr++) {
                uint32_t o[8];
#pragma unroll
                for (int k = 0; k < 8; k++) o[k] = pack_bf16(f[rr][2 * k] * rstd[rr], f[rr][2 * k + 1] * rstd[rr]);
                sts_u4(stg + rr * 1024, make_uint4(o[0], o[1], o[2], o[3]));
                sts_u4(stg + rr * 1024 + 512, make_uint4(o[4], o[5], o[6], o[7]));
            }
            fence_async_smem();
            __syncwarp();
            if (elect_one()) {
                bulk_store(g_xn + (size_t)(b * 16 + cw * 2) * D_, sb + OFF_B + cw * 2048, 2048);
                bulk_commit();
                bulk_wait_all();
            }
            __syncwarp();
            if (ct == 0) TRACE(31);
            named_bar(1, 256);
            if (ct < 8) cnt_add(CN_X + ct);
            if (ct == 0) TRACE(5);
            cluster_wait();
        }
        reg_alloc<216>();
        if (ct == 0) TRACE(30);
        const int cwarp = warp & 3;
        const int r0 = cwarp * 16 + (lane >> 2);
        const int c0 = (lane & 3) * 2;
        const uint32_t abase = sb + OFF_A + w * (NA * 8192);
        const uint32_t fullA = sb + BAR_FULLA + 8 * NA1 * w, emptyA = sb + BAR_EMPTYA + 8 * NA1 * w;
        const uint32_t peer_pemptyA = peer_sb + BAR_PEMPTYA + 8 * NA1 * w;
        const uint32_t fullB = sb + BAR_FULLB, emptyB = sb + BAR_EMPTYB, peer_pemptyB = peer_sb + BAR_PEMPTYB;
        const int sm_row = cwarp * 16 + (lane & 7) + ((lane >> 3) & 1) * 8;
        const int sm_cg = lane >> 4;
        uint32_t pha = 0, phb = 0;

        {
            float acc[64];
#pragma unroll
            for (int i = 0; i < 64; i++) acc[i] = 0.f;
            fence_regs(acc);
            float rsacc[4] = {0.f, 0.f, 0.f, 0.f};
            fence_regs(rsacc);
            const uint64_t d_ones = make_desc(sb + OFF_ONES, 16, 1024);
            int sa = 0, sbb = 0, psa = 0, psb = 0, kb = 0;
            auto step = [&](auto own) {
                mbar_wait(fullA + 8 * sa, bit(pha, sa));
                if (ct == 0) TRACE2(0, kb);
                mbar_wait(fullB + 8 * sbb, bit(phb, sbb));
                if (ct == 0) TRACE2(1, kb);
                if (kb == 0 && ct == 0) TRACE(6);
                uint64_t da = make_desc(a_slot_addr(sb, w, sa), 16, 1024);
                uint64_t db = make_desc(sb + OFF_B + sbb * 16384, 8192, 1024);
                wgmma_fence();
#pragma unroll
                for (int k = 0; k < 4; k++) wgmma_n128<1>(acc, da + k * 2, db + k * 128, 1);
                if (decltype(own)::value) {
#pragma unroll
                    for (int k = 0; k < 4; k++) wgmma_n8<0>(rsacc, da + k * 2, d_ones, 1);
                }
                wgmma_commit();
                wgmma_wait<1>();
                if (kb > 0 && wt == 0) {
                    if (kb - 1 + NA1 < 32 && ((kb - 1) & 1) != rho) mbar_arrive_cl(peer_pemptyA + 8 * psa);
                    if (kb != 27 && kb != 28) mbar_arrive(emptyA + 8 * psa);
                    mbar_arrive(emptyB + 8 * psb);
                }
                pha ^= 1u << sa; phb ^= 1u << sbb;
                psa = sa; psb = sbb;
                if (++sa == NA1) sa = 0;
                if (++sbb == NB1) sbb = 0;
                kb++;
            };
            using Yes = BoolC<true>; using No = BoolC<false>;
#pragma unroll 1
            for (int i = 0; i < nt1; i++) step(No{});
#pragma unroll 1
            for (int g = 0; g < 7; g++) { step(Yes{}); step(No{}); step(No{}); step(No{}); }
            step(Yes{});
#pragma unroll 1
            for (int i = nt1; i < 3; i++) step(No{});
            wgmma_wait<0>();
            fence_regs(acc);
            if (wt == 0) { mbar_arrive(emptyB + 8 * 3); mbar_arrive_cl(peer_pemptyB + 8 * 3); }
            if (wt == 0) mbar_arrive(emptyA + 8 * 1);
            if (ct == 0) TRACE(7);
            fence_regs(rsacc);
            if ((lane & 3) == 0) { sts_f(sb + OFF_RSP + (w * 64 + r0) * 4, rsacc[0]); sts_f(sb + OFF_RSP + (w * 64 + r0 + 8) * 4, rsacc[2]); }
            mbar_wait(sb + BAR_AUX, 0);
            const float sgn = part1 ? -1.f : 1.f;
#pragma unroll
            for (int i = 0; i < 16; i += 2) {
                uint32_t rr[4];
#pragma unroll
                for (int u = 0; u < 2; u++) {
                    float2 ca = lds_f2(sb + OFF_CA1 + ((i + u) * 8 + c0) * 4);
                    ca.x *= sgn; ca.y *= sgn;
                    const float* a = &acc[(i + u) * 4];
                    rr[u * 2 + 0] = pack_bf16(a[0] * ca.x, a[1] * ca.y);
                    rr[u * 2 + 1] = pack_bf16(a[2] * ca.x, a[3] * ca.y);
                }
                int cg = (i & 7) + sm_cg;
                stsm4(abase + (2 + (i >> 3)) * 8192 + sm_row * 128 + ((cg ^ (sm_row & 7)) << 4), rr[0], rr[1], rr[2], rr[3]);
            }
            if (ct == 0) TRACE(41);
            fence_async_smem();
            named_bar(2 + w, 128);
            if (cwarp == 0 && elect_one()) {
                tma_store(&p.m[M_PQ], abase + 2 * 8192, part1 * 512 + nt1 * 128, i1 * 128 + w * 64);
                tma_store(&p.m[M_PQ], abase + 3 * 8192, part1 * 512 + nt1 * 128 + 64, i1 * 128 + w * 64);
                bulk_store(g_rs + (mt1 * 4 + nt1) * 128 + w * 64, sb + OFF_RSP + w * 256, 256);
                bulk_commit();
                if (w == 0) TRACE(43);
                bulk_wait_all();
                if (w == 0) TRACE(44);
                cnt_add(CN_1 + (part1 * 16 + i1) * 2 + w);
                mbar_arrive(emptyA + 8 * 2);
                mbar_arrive(emptyA + 8 * 3);
                if (w == 0) TRACE(8);
            }
            __syncwarp();
        }
        const int col2 = q2 * 128 + rho * 64;
        {
            uint32_t xr[16];
            {
                const __nv_bfloat16* xp = p.x + (size_t)(i2 * 128 + w * 64 + r0) * D_ + col2 + c0;
#pragma unroll
                for (int i = 0; i < 8; i++) {
                    xr[2 * i] = __ldg((const uint32_t*)(xp + i * 8));
                    xr[2 * i + 1] = __ldg((const uint32_t*)(xp + 8 * D_ + i * 8));
                }
            }
            float acc[64];
#pragma unroll
            for (int i = 0; i < 64; i++) acc[i] = 0.f;
            fence_regs(acc);
            int psb = 0;
            float rpa[4], rpb[4];
#pragma unroll 1
            for (int kb = 0; kb < 8; kb++) {
                const int sa = kb & 3, sbb = (P2_SLOTS >> (4 * kb)) & 15;
                mbar_wait(fullA + 8 * sa, bit(pha, sa));
                mbar_wait(fullB + 8 * sbb, bit(phb, sbb));
                if (kb == 0 && ct == 0) TRACE(9);
                if (ct == 0) TRACE2(4, kb);
                if (kb == 0) {
                    const float* rp = g_rs + (rho * 16 + i2) * 512 + w * 64 + r0;
#pragma unroll
                    for (int j = 0; j < 4; j++) { rpa[j] = __ldcg(rp + j * 128); rpb[j] = __ldcg(rp + j * 128 + 8); }
                }
                uint64_t da = make_desc(abase + sa * 8192, 16, 1024);
                uint64_t db = make_desc(sb + OFF_B + sbb * 16384, 16, 1024);
                wgmma_fence();
#pragma unroll
                for (int k = 0; k < 4; k++) wgmma_n128<0>(acc, da + k * 2, db + k * 2, 1);
                wgmma_commit();
                wgmma_wait<1>();
                if (kb > 0 && wt == 0) {
                    if (kb - 1 < 4) mbar_arrive(emptyA + 8 * (kb - 1));
                    if (kb == 6) { mbar_expect_tx(sb + BAR_RFULL + 8 * w, 16384); mbar_arrive_cl(peer_sb + BAR_PRDY + 8 * w); }
                    mbar_arrive(emptyB + 8 * psb); mbar_arrive_cl(peer_pemptyB + 8 * psb);
                }
                pha ^= 1u << sa; phb ^= 1u << sbb;
                psb = sbb;
            }
            wgmma_wait<0>();
            fence_regs(acc);
            if (wt == 0) { mbar_arrive(emptyB + 8 * psb); mbar_arrive_cl(peer_pemptyB + 8 * psb); }
            if (ct == 0) TRACE(10);
            {
                mbar_wait(sb + BAR_AUX + 8, 0);
                const float ra = (rpa[0] + rpa[1]) + (rpa[2] + rpa[3]), rb2 = (rpb[0] + rpb[1]) + (rpb[2] + rpb[3]);
#pragma unroll
                for (int j = 0; j < 16; j++) {
                    float2 v = lds_f2(sb + OFF_SA + (j * 8 + c0) * 4);
                    acc[4 * j] = fmaf(ra, v.x, acc[4 * j]); acc[4 * j + 1] = fmaf(ra, v.y, acc[4 * j + 1]);
                    acc[4 * j + 2] = fmaf(rb2, v.x, acc[4 * j + 2]); acc[4 * j + 3] = fmaf(rb2, v.y, acc[4 * j + 3]);
                }
            }
            mbar_wait(sb + BAR_PRDY + 8 * w, 0);
            {
                uint32_t rdst = peer_sb + OFF_A + w * (NA * 8192) + wt * 16, rbar = peer_sb + BAR_RFULL + 8 * w;
#pragma unroll
                for (int j = 0; j < 8; j++) st_async4(rdst + j * 2048, acc[32 + 4 * j], acc[33 + 4 * j], acc[34 + 4 * j], acc[35 + 4 * j], rbar);
            }
            mbar_wait_cl(sb + BAR_RFULL + 8 * w, 0);
            if (ct == 0) TRACE(45);
            float s0 = 0.f, s1 = 0.f;
            uint32_t zz[16], x2p[16];
#pragma unroll
            for (int j = 0; j < 8; j++) {
                float4 rv = lds_f4(abase + j * 2048 + wt * 16);
                float2 ga = lds_f2(sb + OFF_GA + (j * 8 + c0) * 4);
                float v0 = bf_lo(xr[2 * j]) + ga.x * (acc[4 * j] + rv.x), v1 = bf_hi(xr[2 * j]) + ga.y * (acc[4 * j + 1] + rv.y);
                float v2 = bf_lo(xr[2 * j + 1]) + ga.x * (acc[4 * j + 2] + rv.z), v3 = bf_hi(xr[2 * j + 1]) + ga.y * (acc[4 * j + 3] + rv.w);
                x2p[2 * j] = pack_bf16(v0, v1); x2p[2 * j + 1] = pack_bf16(v2, v3);
                acc[4 * j] = bf_lo(x2p[2 * j]); acc[4 * j + 1] = bf_hi(x2p[2 * j]);
                acc[4 * j + 2] = bf_lo(x2p[2 * j + 1]); acc[4 * j + 3] = bf_hi(x2p[2 * j + 1]);
                s0 += acc[4 * j] + acc[4 * j + 1]; s1 += acc[4 * j + 2] + acc[4 * j + 3];
                float2 cb = lds_f2(sb + OFF_CB1 + (j * 8 + c0) * 4);
                zz[2 * j] = pack_bf16(acc[4 * j] * cb.x, acc[4 * j + 1] * cb.y);
                zz[2 * j + 1] = pack_bf16(acc[4 * j + 2] * cb.x, acc[4 * j + 3] * cb.y);
            }
#pragma unroll
            for (int j = 0; j < 8; j += 2) {
                int cg = j + sm_cg;
                stsm4(abase + 2 * 8192 + sm_row * 128 + ((cg ^ (sm_row & 7)) << 4), zz[2 * j], zz[2 * j + 1], zz[2 * j + 2], zz[2 * j + 3]);
            }
            s0 += __shfl_xor_sync(0xffffffffu, s0, 1); s0 += __shfl_xor_sync(0xffffffffu, s0, 2);
            s1 += __shfl_xor_sync(0xffffffffu, s1, 1); s1 += __shfl_xor_sync(0xffffffffu, s1, 2);
            float m0 = s0 * (1.f / 64.f), m1 = s1 * (1.f / 64.f), q0 = 0.f, q1 = 0.f;
#pragma unroll
            for (int j = 0; j < 8; j++) {
                float d0 = acc[4 * j] - m0, d1 = acc[4 * j + 1] - m0, d2 = acc[4 * j + 2] - m1, d3 = acc[4 * j + 3] - m1;
                q0 += d0 * d0 + d1 * d1; q1 += d2 * d2 + d3 * d3;
            }
            q0 += __shfl_xor_sync(0xffffffffu, q0, 1); q0 += __shfl_xor_sync(0xffffffffu, q0, 2);
            q1 += __shfl_xor_sync(0xffffffffu, q1, 1); q1 += __shfl_xor_sync(0xffffffffu, q1, 2);
            if ((lane & 3) == 0) {
                sts_f2(sb + OFF_ST + w * 512 + r0 * 8, m0, q0);
                sts_f2(sb + OFF_ST + w * 512 + (r0 + 8) * 8, m1, q1);
            }
            fence_async_smem();
            named_bar(2 + w, 128);
            if (cwarp == 0 && elect_one()) {
                tma_store(&p.m[M_Z], abase + 2 * 8192, col2, i2 * 128 + w * 64);
                bulk_store(g_stats + ((i2 * 2 + w) * 8 + q2 * 2 + rho) * 64, sb + OFF_ST + w * 512, 512);
                bulk_commit();
                bulk_wait_all();
                if (w == 0) TRACE(46);
                cnt_add(CN_2 + i2 * 2 + w);
#pragma unroll
                for (int s = 0; s < NA; s++) mbar_arrive(emptyA + 8 * s);
                if (w == 0) TRACE(11);
            }
            uint4* xs = g_x2s + (size_t)(b * 2 + w) * 512 + wt;
#pragma unroll
            for (int j = 0; j < 4; j++) xs[j * 128] = make_uint4(x2p[4 * j], x2p[4 * j + 1], x2p[4 * j + 2], x2p[4 * j + 3]);
        }
        {
            float ag[88], au[88];
#pragma unroll
            for (int i = 0; i < 88; i++) { ag[i] = 0.f; au[i] = 0.f; }
            fence_regs(ag); fence_regs(au);
            int sbb = 3, psb = 0;
            float2 st0[2], st1[2];
#pragma unroll 1
            for (int kb = 0; kb < 8; kb++) {
                const int sa = kb & 3;
                mbar_wait(fullA + 8 * sa, bit(pha, sa));
                if (ct == 0) TRACE2(7, kb);
                mbar_wait(fullB + 8 * sbb, bit(phb, sbb));
                if (kb == 0 && ct == 0) TRACE(12);
                if (ct == 0) TRACE2(4, 8 + kb);
                if (kb == 7) {
                    const float2* sp = g_stats + (size_t)((i3 * 2 + w) * 8 + (lane & 3) * 2) * 64 + r0;
                    st0[0] = __ldcg(sp); st0[1] = __ldcg(sp + 64); st1[0] = __ldcg(sp + 8); st1[1] = __ldcg(sp + 72);
                }
                uint64_t da = make_desc(abase + sa * 8192, 16, 1024);
                uint64_t dg = make_desc(sb + OFF_B + sbb * 16384, 8192, 1024);
                uint64_t du = make_desc(sb + OFF_B + sbb * 16384 + 3 * 8192, 8192, 1024);
                wgmma_fence();
#pragma unroll
                for (int k = 0; k < 4; k++) {
                    wgmma_n176<1>(ag, da + k * 2, dg + k * 128, 1);
                    wgmma_n176<1>(au, da + k * 2, du + k * 128, 1);
                }
                wgmma_commit();
                wgmma_wait<1>();
                if (ct == 0) TRACE2(5, 16 + kb);
                if (ct == 128) TRACE2(5, 24 + kb);
                if (kb > 0 && wt == 0) {
                    if (kb - 1 < 4) mbar_arrive(emptyA + 8 * (kb - 1));
                    mbar_arrive(emptyB + 8 * psb); if (kb - 1 < 5) mbar_arrive_cl(peer_pemptyB + 8 * psb);
                    TRACE2(6, 48 + w * 8 + kb);
                }
                pha ^= 1u << sa; phb ^= 1u << sbb;
                psb = sbb;
                sbb += 3; if (sbb == NB) sbb = 0;
            }
            wgmma_wait<0>();
            fence_regs(ag); fence_regs(au);
            if (wt == 0) mbar_arrive(emptyB + 8 * psb);
            if (ct == 0) TRACE(13);
            float mu0 = st0[0].x + st0[1].x, mu1 = st1[0].x + st1[1].x;
            mu0 += __shfl_xor_sync(0xffffffffu, mu0, 1); mu0 += __shfl_xor_sync(0xffffffffu, mu0, 2);
            mu1 += __shfl_xor_sync(0xffffffffu, mu1, 1); mu1 += __shfl_xor_sync(0xffffffffu, mu1, 2);
            mu0 *= 0.125f; mu1 *= 0.125f;
            float e0 = st0[0].x - mu0, e1 = st0[1].x - mu0, e2 = st1[0].x - mu1, e3 = st1[1].x - mu1;
            float v0 = st0[0].y + st0[1].y + 64.f * (e0 * e0 + e1 * e1), v1 = st1[0].y + st1[1].y + 64.f * (e2 * e2 + e3 * e3);
            v0 += __shfl_xor_sync(0xffffffffu, v0, 1); v0 += __shfl_xor_sync(0xffffffffu, v0, 2);
            v1 += __shfl_xor_sync(0xffffffffu, v1, 1); v1 += __shfl_xor_sync(0xffffffffu, v1, 2);
            const float rs0 = rsqrtf(v0 * (1.f / 512.f) + 1e-5f), rs1 = rsqrtf(v1 * (1.f / 512.f) + 1e-5f);
            const float hg0 = 0.5f * rs0, hg1 = 0.5f * rs1;
            const float ng0 = -hg0 * mu0, ng1 = -hg1 * mu1, nu0 = -rs0 * mu0, nu1 = -rs1 * mu1;
            mbar_wait(sb + BAR_AUX + 16, 0);
            const uint32_t st_base = abase + sm_row * 352 + sm_cg * 16;
#pragma unroll
            for (int i = 0; i < 22; i += 2) {
                uint32_t rr[4];
#pragma unroll
                for (int u = 0; u < 2; u++) {
                    uint32_t t = sb + OFF_T3 + ((i + u) * 4 + (lane & 3)) * 32;
                    float4 tg = lds_f4(t), tu = lds_f4(t + 16);
                    const float* g = &ag[(i + u) * 4];
                    const float* uu = &au[(i + u) * 4];
                    float h[4];
                    {
                        float gg = fmaf(hg0, g[0], fmaf(ng0, tg.x, tg.z)), u_ = fmaf(rs0, uu[0], fmaf(nu0, tu.x, tu.z));
                        h[0] = fmaf(0.5f, tanh_fast(gg), 0.5f) * u_;
                        gg = fmaf(hg0, g[1], fmaf(ng0, tg.y, tg.w)); u_ = fmaf(rs0, uu[1], fmaf(nu0, tu.y, tu.w));
                        h[1] = fmaf(0.5f, tanh_fast(gg), 0.5f) * u_;
                        gg = fmaf(hg1, g[2], fmaf(ng1, tg.x, tg.z)); u_ = fmaf(rs1, uu[2], fmaf(nu1, tu.x, tu.z));
                        h[2] = fmaf(0.5f, tanh_fast(gg), 0.5f) * u_;
                        gg = fmaf(hg1, g[3], fmaf(ng1, tg.y, tg.w)); u_ = fmaf(rs1, uu[3], fmaf(nu1, tu.y, tu.w));
                        h[3] = fmaf(0.5f, tanh_fast(gg), 0.5f) * u_;
                    }
                    rr[u * 2] = pack_bf16(h[0], h[1]); rr[u * 2 + 1] = pack_bf16(h[2], h[3]);
                }
                stsm4(st_base + i * 16, rr[0], rr[1], rr[2], rr[3]);
            }
            if (ct == 0) TRACE(47);
            fence_async_smem();
            named_bar(2 + w, 128);
            if (cwarp == 0 && elect_one()) {
                tma_store(&p.m[M_HST], abase, j3 * 176, i3 * 128 + w * 64);
                bulk_commit();
                bulk_wait_all();
                if (w == 0) TRACE(48);
                cnt_add(CN_3 + (i3 * 2 + (j3 >> 2)) * 2 + w);
#pragma unroll
                for (int s = 0; s < NA; s++) mbar_arrive(emptyA + 8 * s);
                if (w == 0) TRACE(14);
            }
        }
        {
            uint4 xs4[4];
            {
                const uint4* xs = g_x2s + (size_t)(b * 2 + w) * 512 + wt;
#pragma unroll
                for (int j = 0; j < 4; j++) xs4[j] = __ldcg(xs + j * 128);
            }
            float acc[64];
#pragma unroll
            for (int i = 0; i < 64; i++) acc[i] = 0.f;
            fence_regs(acc);
            int sbb = 0, psb = 0;
#pragma unroll 1
            for (int kb = 0; kb < NKB4; kb++) {
                const int sa = kb & 3;
                mbar_wait(fullA + 8 * sa, bit(pha, sa));
                mbar_wait(fullB + 8 * sbb, bit(phb, sbb));
                if (kb == 0 && ct == 0) TRACE(15);
                if (ct == 0) TRACE2(4, 16 + kb);
                uint64_t da = make_desc(abase + sa * 8192, 16, 1024);
                uint64_t db = make_desc(sb + OFF_B + sbb * 16384, 8192, 1024);
                wgmma_fence();
#pragma unroll
                for (int k = 0; k < 4; k++) wgmma_n128<1>(acc, da + k * 2, db + k * 128, 1);
                wgmma_commit();
                wgmma_wait<1>();
                if (kb > 0 && wt == 0) {
                    if (kb - 1 < NKB4 - 4) mbar_arrive(emptyA + 8 * ((kb - 1) & 3));
                    if (kb == 9) { mbar_expect_tx(sb + BAR_RFULL + 8 * w, 16384); mbar_arrive_cl(peer_sb + BAR_PRDY + 8 * w); }
                    mbar_arrive(emptyB + 8 * psb);
                }
                pha ^= 1u << sa; phb ^= 1u << sbb;
                psb = sbb;
                if (++sbb == NB) sbb = 0;
            }
            wgmma_wait<0>();
            fence_regs(acc);
            if (ct == 0) TRACE(16);
            mbar_wait(sb + BAR_PRDY + 8 * w, 1);
            {
                uint32_t rdst = peer_sb + OFF_A + w * (NA * 8192) + wt * 16, rbar = peer_sb + BAR_RFULL + 8 * w;
#pragma unroll
                for (int j = 0; j < 8; j++)
                    st_async4(rdst + (j < 4 ? 3 * 8192 + j * 2048 : (j - 4) * 2048), acc[32 + 4 * j], acc[33 + 4 * j], acc[34 + 4 * j], acc[35 + 4 * j], rbar);
            }
            mbar_wait_cl(sb + BAR_RFULL + 8 * w, 1);
            uint32_t xp[16] = {xs4[0].x, xs4[0].y, xs4[0].z, xs4[0].w, xs4[1].x, xs4[1].y, xs4[1].z, xs4[1].w,
                               xs4[2].x, xs4[2].y, xs4[2].z, xs4[2].w, xs4[3].x, xs4[3].y, xs4[3].z, xs4[3].w};
            uint32_t oo[16];
#pragma unroll
            for (int j = 0; j < 8; j++) {
                float4 rv = lds_f4(abase + (j < 4 ? 3 * 8192 + j * 2048 : (j - 4) * 2048) + wt * 16);
                float2 gb = lds_f2(sb + OFF_GB + (j * 8 + c0) * 4);
                oo[2 * j] = pack_bf16(bf_lo(xp[2 * j]) + gb.x * (acc[4 * j] + rv.x), bf_hi(xp[2 * j]) + gb.y * (acc[4 * j + 1] + rv.y));
                oo[2 * j + 1] = pack_bf16(bf_lo(xp[2 * j + 1]) + gb.x * (acc[4 * j + 2] + rv.z), bf_hi(xp[2 * j + 1]) + gb.y * (acc[4 * j + 3] + rv.w));
            }
#pragma unroll
            for (int j = 0; j < 8; j += 2) {
                int cg = j + sm_cg;
                stsm4(abase + 1 * 8192 + sm_row * 128 + ((cg ^ (sm_row & 7)) << 4), oo[2 * j], oo[2 * j + 1], oo[2 * j + 2], oo[2 * j + 3]);
            }
            fence_async_smem();
            named_bar(2 + w, 128);
            if (cwarp == 0 && elect_one()) {
                tma_store(&p.m[M_OUT], abase + 8192, col2, i2 * 128 + w * 64);
                bulk_commit();
                bulk_wait_all();
                if (w == 0) TRACE(17);
            }
        }
        named_bar(1, 256);
        if (ct == 0) {
            unsigned old = atomicInc(&g_done, NCTA - 1);
            if (old == NCTA - 1) g_epoch = tag;
        }
        cluster_arrive();
        cluster_wait();
    }
}

typedef CUresult (*EncodeFn)(CUtensorMap*, CUtensorMapDataType, cuuint32_t, void*, const cuuint64_t*, const cuuint64_t*, const cuuint32_t*,
                             const cuuint32_t*, CUtensorMapInterleave, CUtensorMapSwizzle, CUtensorMapL2promotion, CUtensorMapFloatOOBfill);

void make_map(EncodeFn enc, CUtensorMap* m, const void* ptr, uint64_t rows, uint64_t cols, uint32_t box_rows, uint32_t box_cols, bool swz) {
    cuuint64_t dims[2] = {cols, rows};
    cuuint64_t strides[1] = {cols * 2};
    cuuint32_t box[2] = {box_cols, box_rows};
    cuuint32_t es[2] = {1, 1};
    enc(m, CU_TENSOR_MAP_DATA_TYPE_BFLOAT16, 2, const_cast<void*>(ptr), dims, strides, box, es, CU_TENSOR_MAP_INTERLEAVE_NONE,
        swz ? CU_TENSOR_MAP_SWIZZLE_128B : CU_TENSOR_MAP_SWIZZLE_NONE, CU_TENSOR_MAP_L2_PROMOTION_L2_256B, CU_TENSOR_MAP_FLOAT_OOB_FILL_NONE);
}

}

extern "C" void kernel_launch(void* const* d_in, const int* in_sizes, int n_in, void* d_out, int out_size) {
    static EncodeFn enc = nullptr;
    static void *pxn, *ppq, *pz, *ph;
    if (!enc) {
        void* fn = nullptr;
        cudaDriverEntryPointQueryResult q;
        cudaGetDriverEntryPoint("cuTensorMapEncodeTiled", &fn, cudaEnableDefault, &q);
        enc = (EncodeFn)fn;
        cudaGetSymbolAddress(&pxn, g_xn);
        cudaGetSymbolAddress(&ppq, g_pq);
        cudaGetSymbolAddress(&pz, g_z);
        cudaGetSymbolAddress(&ph, g_h);
        cudaFuncSetAttribute(mega_kernel, cudaFuncAttributeMaxDynamicSharedMemorySize, SMEM_BYTES);
    }
    Params p = {};
    p.x = (const __nv_bfloat16*)d_in[0];
    p.wre = (const __nv_bfloat16*)d_in[1];
    p.wim = (const __nv_bfloat16*)d_in[2];
    p.dr = (const __nv_bfloat16*)d_in[3];
    p.di = (const __nv_bfloat16*)d_in[4];
    p.wg = (const __nv_bfloat16*)d_in[6];
    p.wu = (const __nv_bfloat16*)d_in[7];
    p.wd = (const __nv_bfloat16*)d_in[8];
    p.c = (const __nv_bfloat16*)d_in[9];
    p.wmod = (const __nv_bfloat16*)d_in[10];
    make_map(enc, &p.m[M_WRE], d_in[1], S_, S_, 64, 64, true);
    make_map(enc, &p.m[M_WIM], d_in[2], S_, S_, 64, 64, true);
    make_map(enc, &p.m[M_XN], pxn, S_, D_, 64, 64, true);
    make_map(enc, &p.m[M_PQ], ppq, S_, 2 * D_, 64, 64, true);
    make_map(enc, &p.m[M_DR], d_in[3], D_, D_, 64, 64, true);
    make_map(enc, &p.m[M_DI], d_in[4], D_, D_, 64, 64, true);
    make_map(enc, &p.m[M_Z], pz, S_, D_, 64, 64, true);
    make_map(enc, &p.m[M_WG], d_in[6], D_, F_, 64, 64, true);
    make_map(enc, &p.m[M_WU], d_in[7], D_, F_, 64, 64, true);
    make_map(enc, &p.m[M_HLD], ph, S_, F_, 64, 64, true);
    make_map(enc, &p.m[M_HST], ph, S_, F_, 64, 176, false);
    make_map(enc, &p.m[M_WD], d_in[8], F_, D_, 64, 64, true);
    make_map(enc, &p.m[M_OUT], d_out, S_, D_, 64, 64, true);
    make_map(enc, &p.m[M_WMOD], d_in[10], D_, 6 * D_, 64, 32, false);
    make_map(enc, &p.m[M_WG32], d_in[6], D_, F_, 64, 32, false);
    make_map(enc, &p.m[M_WU32], d_in[7], D_, F_, 64, 32, false);

    cudaLaunchConfig_t cfg = {};
    cfg.gridDim = dim3(NCTA);
    cfg.blockDim = dim3(384);
    cfg.dynamicSmemBytes = SMEM_BYTES;
    cfg.stream = cudaStreamPerThread;
    cudaLaunchAttribute at[1];
    at[0].id = cudaLaunchAttributeClusterDimension;
    at[0].val.clusterDim.x = 2; at[0].val.clusterDim.y = 1; at[0].val.clusterDim.z = 1;
    cfg.attrs = at; cfg.numAttrs = 1;
    cudaLaunchKernelEx(&cfg, mega_kernel, p);
}
```

```cpp
#include <cuda_runtime.h>
#include <cuda_bf16.h>
#include <cuda.h>
#include <stdint.h>

namespace {

constexpr int S_ = 2048, D_ = 512, F_ = 1376;
constexpr int NCTA = 128;
constexpr int NAUX = 4;
constexpr int NB = 9;
constexpr int NA = 4;
constexpr int NA1 = 6;
constexpr int NB1 = 7;
constexpr uint32_t OFF_B = 0;
constexpr uint32_t OFF_A = NB * 16384;
constexpr uint32_t OFF_AUX = OFF_A + 2 * NA * 8192;
constexpr uint32_t OFF_ONES = OFF_AUX;
constexpr uint32_t OFF_CA1 = OFF_ONES + 1024;
constexpr uint32_t OFF_SA = OFF_CA1 + 128 * 4;
constexpr uint32_t OFF_GA = OFF_SA + 128 * 16;
constexpr uint32_t OFF_CB1 = OFF_GA + 64 * 4;
constexpr uint32_t OFF_GB = OFF_CB1 + 64 * 4;
constexpr uint32_t OFF_BX = OFF_GB + 64 * 4;
constexpr uint32_t OFF_AX = OFF_BX + 2 * 176 * 16;
constexpr uint32_t OFF_ZERO = OFF_AX + 2048;
constexpr uint32_t OFF_ST = OFF_ZERO + 1024;
constexpr uint32_t OFF_RSP = OFF_ST + 1024;
constexpr uint32_t OFF_BAR = OFF_RSP + 512;
constexpr uint32_t BAR_FULLB = OFF_BAR;
constexpr uint32_t BAR_EMPTYB = BAR_FULLB + 8 * NB;
constexpr uint32_t BAR_FULLA = BAR_EMPTYB + 8 * NB;
constexpr uint32_t BAR_EMPTYA = BAR_FULLA + 16 * NA1;
constexpr uint32_t BAR_PEMPTYA = BAR_EMPTYA + 16 * NA1;
constexpr uint32_t BAR_PRDY = BAR_PEMPTYA + 16 * NA1;
constexpr uint32_t BAR_RFULL = BAR_PRDY + 16;
constexpr uint32_t BAR_AUX = BAR_RFULL + 16;
constexpr uint32_t BAR_DEP = BAR_AUX + 24;
constexpr uint32_t BAR_STG = BAR_DEP + 16;
constexpr uint32_t BAR_XARR = BAR_STG + 32;
constexpr uint32_t SMEM_USED = BAR_XARR + 8;
constexpr uint32_t SMEM_BYTES = SMEM_USED;
static_assert(SMEM_BYTES <= 232448, "smem");
constexpr uint32_t P2_SLOTS = 4u | (5u << 4) | (6u << 8) | (0u << 12) | (7u << 16) | (8u << 20) | (1u << 24) | (2u << 28);

enum { M_WRE = 0, M_WIM, M_XN, M_PQ, M_DR, M_DI, M_Z, M_WG, M_WU, M_WD, M_OUT, M_WMODS, M_COUNT };

struct alignas(64) Params {
    const __nv_bfloat16* x;
    const __nv_bfloat16* c;
    const __nv_bfloat16* wmod;
    const __nv_bfloat16* wg;
    const __nv_bfloat16* wu;
    const __nv_bfloat16* dr;
    const __nv_bfloat16* di;
    const __nv_bfloat16* wd;
    const __nv_bfloat16* wre;
    const __nv_bfloat16* wim;
    const void* pad[6];
    CUtensorMap m[M_COUNT];
};

constexpr int CN_X = 0;
constexpr int CN_MOD = 8;
constexpr int CN_V = 10;
constexpr int CN_CS = 12;
constexpr int CN_1 = 16;
constexpr int CN_2 = CN_1 + 64;
constexpr int CN_3 = CN_2 + 32;
constexpr int CN_2S = CN_3 + 64;
constexpr int CN_COUNT = CN_2S + 32;

}

__device__ __align__(1024) __nv_bfloat16 g_xn[S_ * D_];
__device__ __align__(1024) __nv_bfloat16 g_pq[S_ * 2 * D_];
__device__ __align__(1024) __nv_bfloat16 g_z[S_ * D_];
__device__ __align__(1024) uint8_t g_h[32 * 8 * 3 * 8192];
__device__ __align__(1024) uint4 g_x2s[NCTA * 2 * 4 * 128];
__device__ __align__(1024) float2 g_stats[S_ * 8];
__device__ __align__(1024) float g_mod[6 * D_];
__device__ __align__(1024) float g_cs[4 * F_];
__device__ __align__(1024) float g_v[2 * D_];
__device__ __align__(1024) float g_rs[32 * 4 * 128];
__device__ __align__(1024) unsigned g_cnt[CN_COUNT * 32];
#define PROG(n) do {} while (0)
__device__ unsigned g_epoch;
__device__ unsigned g_done;
#define TRACE_INIT() do {} while (0)
#define TRACE(slot) do {} while (0)
#define TRACE2(ev, idx) do {} while (0)
#define TRACE_GT(slot) do {} while (0)

namespace {

__device__ __forceinline__ uint32_t smem_u32(const void* p) { return (uint32_t)__cvta_generic_to_shared(p); }
__device__ __forceinline__ void mbar_init(uint32_t bar, uint32_t cnt) { asm volatile("mbarrier.init.shared::cta.b64 [%0], %1;" :: "r"(bar), "r"(cnt) : "memory"); }
__device__ __forceinline__ void mbar_expect_tx(uint32_t bar, uint32_t bytes) { asm volatile("mbarrier.arrive.expect_tx.shared::cta.b64 _, [%0], %1;" :: "r"(bar), "r"(bytes) : "memory"); }
__device__ __forceinline__ void mbar_arrive(uint32_t bar) { asm volatile("mbarrier.arrive.shared::cta.b64 _, [%0];" :: "r"(bar) : "memory"); }
__device__ __forceinline__ uint32_t mapa(uint32_t addr, uint32_t cta) { uint32_t r; asm volatile("mapa.shared::cluster.u32 %0, %1, %2;" : "=r"(r) : "r"(addr), "r"(cta)); return r; }
__device__ __forceinline__ void mbar_arrive_cl(uint32_t cl_addr) { asm volatile("mbarrier.arrive.shared::cluster.b64 _, [%0];" :: "r"(cl_addr) : "memory"); }
__device__ __forceinline__ void mbar_wait(uint32_t bar, uint32_t parity) {
    asm volatile("{\n.reg .pred p;\n.reg .u32 c;\nmov.u32 c, 0;\n"
                 "MW_LOOP:\nmbarrier.try_wait.parity.shared::cta.b64 p, [%0], %1;\n@p bra MW_DONE;\n"
                 "add.u32 c, c, 1;\nsetp.lt.u32 p, c, 3000000;\n@p bra MW_LOOP;\ntrap;\nMW_DONE:\n}" :: "r"(bar), "r"(parity) : "memory");
}
__device__ __forceinline__ void mbar_wait_cl(uint32_t bar, uint32_t parity) {
    asm volatile("{\n.reg .pred p;\n.reg .u32 c;\nmov.u32 c, 0;\n"
                 "MW_LOOP:\nmbarrier.try_wait.parity.acquire.cluster.shared::cta.b64 p, [%0], %1;\n@p bra MW_DONE;\n"
                 "add.u32 c, c, 1;\nsetp.lt.u32 p, c, 3000000;\n@p bra MW_LOOP;\ntrap;\nMW_DONE:\n}" :: "r"(bar), "r"(parity) : "memory");
}
__device__ __forceinline__ void tma_load(uint32_t dst, const CUtensorMap* map, int c0, int c1, uint32_t bar) {
    asm volatile("cp.async.bulk.tensor.2d.shared::cluster.global.mbarrier::complete_tx::bytes [%0], [%1, {%3, %4}], [%2];"
                 :: "r"(dst), "l"(map), "r"(bar), "r"(c0), "r"(c1) : "memory");
}
__device__ __forceinline__ void tma_load_mc(uint32_t dst, const CUtensorMap* map, int c0, int c1, uint32_t bar) {
    asm volatile("cp.async.bulk.tensor.2d.shared::cluster.global.mbarrier::complete_tx::bytes.multicast::cluster [%0], [%1, {%3, %4}], [%2], %5;"
                 :: "r"(dst), "l"(map), "r"(bar), "r"(c0), "r"(c1), "h"((uint16_t)3) : "memory");
}
__device__ __forceinline__ void prefetch_tmap(const CUtensorMap* m) { asm volatile("prefetch.tensormap [%0];" :: "l"(m) : "memory"); }
__device__ __forceinline__ void bulk_prefetch(const void* p, uint32_t bytes) {
    asm volatile("cp.async.bulk.prefetch.L2.global [%0], %1;" :: "l"(p), "r"(bytes) : "memory");
}
__device__ __forceinline__ void tma_store(const CUtensorMap* map, uint32_t src, int c0, int c1) {
    asm volatile("cp.async.bulk.tensor.2d.global.shared::cta.bulk_group [%0, {%2, %3}], [%1];" :: "l"(map), "r"(src), "r"(c0), "r"(c1) : "memory");
}
__device__ __forceinline__ void bulk_commit() { asm volatile("cp.async.bulk.commit_group;" ::: "memory"); }
__device__ __forceinline__ void bulk_wait_all() { asm volatile("cp.async.bulk.wait_group 0;" ::: "memory"); }
__device__ __forceinline__ void fence_async_smem() { asm volatile("fence.proxy.async.shared::cta;" ::: "memory"); }
__device__ __forceinline__ void fence_async_global() { asm volatile("fence.proxy.async.global;" ::: "memory"); }
__device__ __forceinline__ bool elect_one() {
    uint32_t pred;
    asm volatile("{\n.reg .pred p;\nelect.sync _|p, 0xffffffff;\nselp.u32 %0, 1, 0, p;\n}" : "=r"(pred));
    return pred != 0;
}
__device__ __forceinline__ void cluster_arrive() { asm volatile("barrier.cluster.arrive.relaxed.aligned;" ::: "memory"); }
__device__ __forceinline__ void cluster_wait() { asm volatile("barrier.cluster.wait.aligned;" ::: "memory"); }
__device__ __forceinline__ void named_bar(int id, int n) { asm volatile("bar.sync %0, %1;" :: "r"(id), "r"(n) : "memory"); }
__device__ __forceinline__ void wgmma_fence() { asm volatile("wgmma.fence.sync.aligned;" ::: "memory"); }
__device__ __forceinline__ void wgmma_commit() { asm volatile("wgmma.commit_group.sync.aligned;" ::: "memory"); }
template <int N> __device__ __forceinline__ void wgmma_wait() { asm volatile("wgmma.wait_group.sync.aligned %0;" :: "n"(N) : "memory"); }
template <int R> __device__ __forceinline__ void reg_alloc() { asm volatile("setmaxnreg.inc.sync.aligned.u32 %0;" :: "n"(R)); }
template <int R> __device__ __forceinline__ void reg_dealloc() { asm volatile("setmaxnreg.dec.sync.aligned.u32 %0;" :: "n"(R)); }
__device__ __forceinline__ unsigned ld_relaxed(const unsigned* p) { unsigned v; asm volatile("ld.relaxed.gpu.global.u32 %0, [%1];" : "=r"(v) : "l"(p) : "memory"); return v; }
__device__ __forceinline__ void bulk_load(uint32_t dst, const void* g, uint32_t bytes, uint32_t bar) {
    asm volatile("cp.async.bulk.shared::cluster.global.mbarrier::complete_tx::bytes [%0], [%1], %2, [%3];" :: "r"(dst), "l"(g), "r"(bytes), "r"(bar) : "memory");
}
__device__ __forceinline__ void bulk_store(void* g, uint32_t src, uint32_t bytes) {
    asm volatile("cp.async.bulk.global.shared::cta.bulk_group [%0], [%1], %2;" :: "l"(g), "r"(src), "r"(bytes) : "memory");
}
__device__ __forceinline__ void sts_u4(uint32_t a, uint4 v) { asm volatile("st.shared.v4.u32 [%0], {%1, %2, %3, %4};" :: "r"(a), "r"(v.x), "r"(v.y), "r"(v.z), "r"(v.w) : "memory"); }
__device__ __forceinline__ void sts_f2(uint32_t a, float x, float y) { asm volatile("st.shared.v2.f32 [%0], {%1, %2};" :: "r"(a), "f"(x), "f"(y) : "memory"); }
__device__ __forceinline__ uint4 ldg_stream(const void* p) {
    uint4 v; asm volatile("ld.global.nc.L1::no_allocate.v4.u32 {%0, %1, %2, %3}, [%4];" : "=r"(v.x), "=r"(v.y), "=r"(v.z), "=r"(v.w) : "l"(p)); return v;
}
__device__ __forceinline__ uint64_t make_desc(uint32_t addr, uint32_t lbo, uint32_t sbo) {
    return (uint64_t)((addr & 0x3FFFF) >> 4) | ((uint64_t)(lbo >> 4) << 16) | ((uint64_t)(sbo >> 4) << 32) | ((uint64_t)1 << 62);
}
__device__ __forceinline__ uint64_t make_desc_ns(uint32_t addr, uint32_t lbo, uint32_t sbo) {
    return (uint64_t)((addr & 0x3FFFF) >> 4) | ((uint64_t)((lbo & 0x3FFFF) >> 4) << 16) | ((uint64_t)(sbo >> 4) << 32);
}
__device__ __forceinline__ uint32_t pack_bf16(float lo, float hi) {
    uint32_t r; asm("cvt.rn.bf16x2.f32 %0, %1, %2;" : "=r"(r) : "f"(hi), "f"(lo)); return r;
}
__device__ __forceinline__ float bf_lo(uint32_t v) { return __uint_as_float(v << 16); }
__device__ __forceinline__ float bf_hi(uint32_t v) { return __uint_as_float(v & 0xffff0000u); }
__device__ __forceinline__ void split_bf16(float v, uint32_t& hi, uint32_t& lo) {
    const __nv_bfloat16 h = __float2bfloat16_rn(v);
    hi = __bfloat16_as_ushort(h);
    lo = __bfloat16_as_ushort(__float2bfloat16_rn(v - __bfloat162float(h)));
}
__device__ __forceinline__ float bf_round(float v) { return __bfloat162float(__float2bfloat16_rn(v)); }
__device__ __forceinline__ void stsm4(uint32_t addr, uint32_t r0, uint32_t r1, uint32_t r2, uint32_t r3) {
    asm volatile("stmatrix.sync.aligned.m8n8.x4.shared.b16 [%0], {%1, %2, %3, %4};" :: "r"(addr), "r"(r0), "r"(r1), "r"(r2), "r"(r3));
}
__device__ __forceinline__ uint4 lds_u4(uint32_t a) { uint4 v; asm volatile("ld.shared.v4.u32 {%0, %1, %2, %3}, [%4];" : "=r"(v.x), "=r"(v.y), "=r"(v.z), "=r"(v.w) : "r"(a)); return v; }
__device__ __forceinline__ void sts_f(uint32_t a, float v) { asm volatile("st.shared.f32 [%0], %1;" :: "r"(a), "f"(v) : "memory"); }
__device__ __forceinline__ void st_async4u(uint32_t cl_addr, uint32_t a, uint32_t b, uint32_t c, uint32_t d, uint32_t cl_bar) {
    asm volatile("st.async.weak.shared::cluster.mbarrier::complete_tx::bytes.v4.b32 [%0], {%1, %2, %3, %4}, [%5];"
                 :: "r"(cl_addr), "r"(a), "r"(b), "r"(c), "r"(d), "r"(cl_bar) : "memory");
}
__device__ __forceinline__ float tanh_fast(float x) { float y; asm("tanh.approx.f32 %0, %1;" : "=f"(y) : "f"(x)); return y; }
template <int N> __device__ __forceinline__ void fence_regs(float (&a)[N]) {
#pragma unroll
    for (int i = 0; i < N; i++) asm volatile("" : "+f"(a[i]) :: "memory");
}
__device__ __forceinline__ void cnt_add(int idx) { asm volatile("red.relaxed.gpu.global.add.u32 [%0], 1;" :: "l"(g_cnt + idx * 32) : "memory"); }
template <int SLEEP_NS>
__device__ __forceinline__ void cnt_wait(int idx, unsigned tag, unsigned per) {
    const unsigned target = tag * per;
    const unsigned* c = g_cnt + idx * 32;
    unsigned it = 0;
    while ((int)(ld_relaxed(c) - target) < 0) {
        if (SLEEP_NS > 0) __nanosleep(SLEEP_NS);
        if (++it > 4000000u) __trap();
    }
    asm volatile("fence.acquire.gpu;" ::: "memory");
}

template <int TB>
__device__ __forceinline__ void wgmma_n128(float (&d)[64], uint64_t da, uint64_t db, int scale_d) {
    asm volatile("{\n.reg .pred p;\nsetp.ne.b32 p, %66, 0;\n"
        "wgmma.mma_async.sync.aligned.m64n128k16.f32.bf16.bf16 {"
        "%0, %1, %2, %3, %4, %5, %6, %7, %8, %9, %10, %11, %12, %13, %14, %15, "
        "%16, %17, %18, %19, %20, %21, %22, %23, %24, %25, %26, %27, %28, %29, %30, %31, "
        "%32, %33, %34, %35, %36, %37, %38, %39, %40, %41, %42, %43, %44, %45, %46, %47, "
        "%48, %49, %50, %51, %52, %53, %54, %55, %56, %57, %58, %59, %60, %61, %62, %63}, "
        "%64, %65, p, 1, 1, 0, %67;\n}"
        : "+f"(d[0]), "+f"(d[1]), "+f"(d[2]), "+f"(d[3]), "+f"(d[4]), "+f"(d[5]), "+f"(d[6]), "+f"(d[7]),
          "+f"(d[8]), "+f"(d[9]), "+f"(d[10]), "+f"(d[11]), "+f"(d[12]), "+f"(d[13]), "+f"(d[14]), "+f"(d[15]),
          "+f"(d[16]), "+f"(d[17]), "+f"(d[18]), "+f"(d[19]), "+f"(d[20]), "+f"(d[21]), "+f"(d[22]), "+f"(d[23]),
          "+f"(d[24]), "+f"(d[25]), "+f"(d[26]), "+f"(d[27]), "+f"(d[28]), "+f"(d[29]), "+f"(d[30]), "+f"(d[31]),
          "+f"(d[32]), "+f"(d[33]), "+f"(d[34]), "+f"(d[35]), "+f"(d[36]), "+f"(d[37]), "+f"(d[38]), "+f"(d[39]),
          "+f"(d[40]), "+f"(d[41]), "+f"(d[42]), "+f"(d[43]), "+f"(d[44]), "+f"(d[45]), "+f"(d[46]), "+f"(d[47]),
          "+f"(d[48]), "+f"(d[49]), "+f"(d[50]), "+f"(d[51]), "+f"(d[52]), "+f"(d[53]), "+f"(d[54]), "+f"(d[55]),
          "+f"(d[56]), "+f"(d[57]), "+f"(d[58]), "+f"(d[59]), "+f"(d[60]), "+f"(d[61]), "+f"(d[62]), "+f"(d[63])
        : "l"(da), "l"(db), "r"(scale_d), "n"(TB));
}
template <int TB>
__device__ __forceinline__ void wgmma_n176(float (&d)[88], uint64_t da, uint64_t db, int scale_d) {
    asm volatile("{\n.reg .pred p;\nsetp.ne.b32 p, %90, 0;\n"
        "wgmma.mma_async.sync.aligned.m64n176k16.f32.bf16.bf16 {"
        "%0, %1, %2, %3, %4, %5, %6, %7, %8, %9, %10, %11, %12, %13, %14, %15, "
        "%16, %17, %18, %19, %20, %21, %22, %23, %24, %25, %26, %27, %28, %29, %30, %31, "
        "%32, %33, %34, %35, %36, %37, %38, %39, %40, %41, %42, %43, %44, %45, %46, %47, "
        "%48, %49, %50, %51, %52, %53, %54, %55, %56, %57, %58, %59, %60, %61, %62, %63, "
        "%64, %65, %66, %67, %68, %69, %70, %71, %72, %73, %74, %75, %76, %77, %78, %79, "
        "%80, %81, %82, %83, %84, %85, %86, %87}, "
        "%88, %89, p, 1, 1, 0, %91;\n}"
        : "+f"(d[0]), "+f"(d[1]), "+f"(d[2]), "+f"(d[3]), "+f"(d[4]), "+f"(d[5]), "+f"(d[6]), "+f"(d[7]),
          "+f"(d[8]), "+f"(d[9]), "+f"(d[10]), "+f"(d[11]), "+f"(d[12]), "+f"(d[13]), "+f"(d[14]), "+f"(d[15]),
          "+f"(d[16]), "+f"(d[17]), "+f"(d[18]), "+f"(d[19]), "+f"(d[20]), "+f"(d[21]), "+f"(d[22]), "+f"(d[23]),
          "+f"(d[24]), "+f"(d[25]), "+f"(d[26]), "+f"(d[27]), "+f"(d[28]), "+f"(d[29]), "+f"(d[30]), "+f"(d[31]),
          "+f"(d[32]), "+f"(d[33]), "+f"(d[34]), "+f"(d[35]), "+f"(d[36]), "+f"(d[37]), "+f"(d[38]), "+f"(d[39]),
          "+f"(d[40]), "+f"(d[41]), "+f"(d[42]), "+f"(d[43]), "+f"(d[44]), "+f"(d[45]), "+f"(d[46]), "+f"(d[47]),
          "+f"(d[48]), "+f"(d[49]), "+f"(d[50]), "+f"(d[51]), "+f"(d[52]), "+f"(d[53]), "+f"(d[54]), "+f"(d[55]),
          "+f"(d[56]), "+f"(d[57]), "+f"(d[58]), "+f"(d[59]), "+f"(d[60]), "+f"(d[61]), "+f"(d[62]), "+f"(d[63]),
          "+f"(d[64]), "+f"(d[65]), "+f"(d[66]), "+f"(d[67]), "+f"(d[68]), "+f"(d[69]), "+f"(d[70]), "+f"(d[71]),
          "+f"(d[72]), "+f"(d[73]), "+f"(d[74]), "+f"(d[75]), "+f"(d[76]), "+f"(d[77]), "+f"(d[78]), "+f"(d[79]),
          "+f"(d[80]), "+f"(d[81]), "+f"(d[82]), "+f"(d[83]), "+f"(d[84]), "+f"(d[85]), "+f"(d[86]), "+f"(d[87])
        : "l"(da), "l"(db), "r"(scale_d), "n"(TB));
}
template <int TB>
__device__ __forceinline__ void wgmma_n8(float (&d)[4], uint64_t da, uint64_t db, int scale_d) {
    asm volatile("{\n.reg .pred p;\nsetp.ne.b32 p, %6, 0;\n"
        "wgmma.mma_async.sync.aligned.m64n8k16.f32.bf16.bf16 {"
        "%0, %1, %2, %3}, "
        "%4, %5, p, 1, 1, 0, %7;\n}"
        : "+f"(d[0]), "+f"(d[1]), "+f"(d[2]), "+f"(d[3])
        : "l"(da), "l"(db), "r"(scale_d), "n"(TB));
}
template <int TB>
__device__ __forceinline__ void wgmma_n256(float (&d)[128], uint64_t da, uint64_t db, int scale_d) {
    asm volatile("{\n.reg .pred p;\nsetp.ne.b32 p, %130, 0;\n"
        "wgmma.mma_async.sync.aligned.m64n256k16.f32.bf16.bf16 {"
        "%0, %1, %2, %3, %4, %5, %6, %7, %8, %9, %10, %11, %12, %13, %14, %15, "
        "%16, %17, %18, %19, %20, %21, %22, %23, %24, %25, %26, %27, %28, %29, %30, %31, "
        "%32, %33, %34, %35, %36, %37, %38, %39, %40, %41, %42, %43, %44, %45, %46, %47, "
        "%48, %49, %50, %51, %52, %53, %54, %55, %56, %57, %58, %59, %60, %61, %62, %63, "
        "%64, %65, %66, %67, %68, %69, %70, %71, %72, %73, %74, %75, %76, %77, %78, %79, "
        "%80, %81, %82, %83, %84, %85, %86, %87, %88, %89, %90, %91, %92, %93, %94, %95, "
        "%96, %97, %98, %99, %100, %101, %102, %103, %104, %105, %106, %107, %108, %109, %110, %111, "
        "%112, %113, %114, %115, %116, %117, %118, %119, %120, %121, %122, %123, %124, %125, %126, %127}, "
        "%128, %129, p, 1, 1, 0, %131;\n}"
        : "+f"(d[0]), "+f"(d[1]), "+f"(d[2]), "+f"(d[3]), "+f"(d[4]), "+f"(d[5]), "+f"(d[6]), "+f"(d[7]),
          "+f"(d[8]), "+f"(d[9]), "+f"(d[10]), "+f"(d[11]), "+f"(d[12]), "+f"(d[13]), "+f"(d[14]), "+f"(d[15]),
          "+f"(d[16]), "+f"(d[17]), "+f"(d[18]), "+f"(d[19]), "+f"(d[20]), "+f"(d[21]), "+f"(d[22]), "+f"(d[23]),
          "+f"(d[24]), "+f"(d[25]), "+f"(d[26]), "+f"(d[27]), "+f"(d[28]), "+f"(d[29]), "+f"(d[30]), "+f"(d[31]),
          "+f"(d[32]), "+f"(d[33]), "+f"(d[34]), "+f"(d[35]), "+f"(d[36]), "+f"(d[37]), "+f"(d[38]), "+f"(d[39]),
          "+f"(d[40]), "+f"(d[41]), "+f"(d[42]), "+f"(d[43]), "+f"(d[44]), "+f"(d[45]), "+f"(d[46]), "+f"(d[47]),
          "+f"(d[48]), "+f"(d[49]), "+f"(d[50]), "+f"(d[51]), "+f"(d[52]), "+f"(d[53]), "+f"(d[54]), "+f"(d[55]),
          "+f"(d[56]), "+f"(d[57]), "+f"(d[58]), "+f"(d[59]), "+f"(d[60]), "+f"(d[61]), "+f"(d[62]), "+f"(d[63]),
          "+f"(d[64]), "+f"(d[65]), "+f"(d[66]), "+f"(d[67]), "+f"(d[68]), "+f"(d[69]), "+f"(d[70]), "+f"(d[71]),
          "+f"(d[72]), "+f"(d[73]), "+f"(d[74]), "+f"(d[75]), "+f"(d[76]), "+f"(d[77]), "+f"(d[78]), "+f"(d[79]),
          "+f"(d[80]), "+f"(d[81]), "+f"(d[82]), "+f"(d[83]), "+f"(d[84]), "+f"(d[85]), "+f"(d[86]), "+f"(d[87]),
          "+f"(d[88]), "+f"(d[89]), "+f"(d[90]), "+f"(d[91]), "+f"(d[92]), "+f"(d[93]), "+f"(d[94]), "+f"(d[95]),
          "+f"(d[96]), "+f"(d[97]), "+f"(d[98]), "+f"(d[99]), "+f"(d[100]), "+f"(d[101]), "+f"(d[102]), "+f"(d[103]),
          "+f"(d[104]), "+f"(d[105]), "+f"(d[106]), "+f"(d[107]), "+f"(d[108]), "+f"(d[109]), "+f"(d[110]), "+f"(d[111]),
          "+f"(d[112]), "+f"(d[113]), "+f"(d[114]), "+f"(d[115]), "+f"(d[116]), "+f"(d[117]), "+f"(d[118]), "+f"(d[119]),
          "+f"(d[120]), "+f"(d[121]), "+f"(d[122]), "+f"(d[123]), "+f"(d[124]), "+f"(d[125]), "+f"(d[126]), "+f"(d[127])
        : "l"(da), "l"(db), "r"(scale_d), "n"(TB));
}

template <bool B> struct BoolC { static constexpr bool value = B; };
template <int I> struct IntC { static constexpr int value = I; };
__device__ __forceinline__ uint32_t bit(uint32_t mask, int i) { return (mask >> i) & 1u; }
__device__ __forceinline__ uint32_t a_slot_addr(uint32_t sb, int w, int slot) {
    return slot < NA ? sb + OFF_A + w * (NA * 8192) + slot * 8192 : sb + OFF_B + (7 + w) * 16384 + (slot - NA) * 8192;
}

constexpr int AX_NS = 5;
constexpr uint32_t AX_A = AX_NS * 32768;
constexpr uint32_t AX_OUT = AX_A + 3 * 8192;
constexpr uint32_t AX_BAR = AX_OUT + 6144;
__device__ __forceinline__ void aux_put_a(uint8_t* smem, int which, int row, int d, float v) {
    const int kb = d >> 6, c = d & 63;
    *(__nv_bfloat16*)(smem + AX_A + which * 8192 + kb * 1024 + row * 128 + (((c >> 3) ^ row) << 4) + (c & 7) * 2) = __float2bfloat16_rn(v);
}
__device__ __forceinline__ void aux_cta(const Params& p, uint8_t* smem, uint32_t sb, int a, unsigned tag, long long t_base_) {
    const int tid = threadIdx.x, lane = tid & 31;
    const int warp = __shfl_sync(0xffffffffu, tid >> 5, 0);
    if (tid == 0) {
        for (int s = 0; s < AX_NS; s++) { mbar_init(sb + AX_BAR + 8 * s, 1); mbar_init(sb + AX_BAR + 8 * (AX_NS + s), 1); }
        asm volatile("fence.mbarrier_init.release.cluster;" ::: "memory");
    }
    for (int i = tid; i < 3 * 8192 / 16; i += 384) *(uint4*)(smem + AX_A + i * 16) = make_uint4(0, 0, 0, 0);
    __syncthreads();
    if (warp == 0) {
        if (elect_one()) {
            const CUtensorMap* mw = &p.m[a < 2 ? M_WG : M_WU];
            const CUtensorMap* md = &p.m[a < 2 ? M_DR : M_DI];
            int slot = 0; uint32_t ph = 1;
#pragma unroll 1
            for (int st = 0; st < 48; st++) {
                const uint32_t full = sb + AX_BAR + 8 * slot, dst = sb + slot * 32768;
                mbar_wait(sb + AX_BAR + 8 * (AX_NS + slot), ph);
                mbar_expect_tx(full, 32768);
                const int kb = st & 7;
#pragma unroll
                for (int c = 0; c < 4; c++) {
                    if (st < 24) tma_load(dst + c * 8192, &p.m[M_WMODS], a * 768 + (st >> 3) * 256 + c * 64, kb * 64, full);
                    else if (st < 32) tma_load(dst + c * 8192, md, kb * 64, (a & 1) * 256 + c * 64, full);
                    else tma_load(dst + c * 8192, mw, (a & 1) * 688 + ((st - 32) >> 3) * 256 + c * 64, kb * 64, full);
                }
                if (++slot == AX_NS) { slot = 0; ph ^= 1; }
            }
        }
        return;
    }
    if (warp < 4) return;
    if (warp >= 8) {
        const int t = tid - 256, cg = t % 22, rq = t / 22;
        named_bar(2, 256);
        float* red = (float*)(smem + AX_OUT + 6144 + 256);
        if (rq < 4) {
            const __nv_bfloat16* W = (a < 2 ? p.wg : p.wu) + (size_t)(rq * 128) * F_ + (a & 1) * 688 + 512 + cg * 8;
            float cs[8], bi[8];
#pragma unroll
            for (int e = 0; e < 8; e++) { cs[e] = 0.f; bi[e] = 0.f; }
#pragma unroll 1
            for (int r0 = 0; r0 < 128; r0 += 16) {
                uint4 v[16]; float m1[16], m0[16];
#pragma unroll
                for (int k = 0; k < 16; k++) v[k] = ldg_stream(W + (size_t)(r0 + k) * F_);
#pragma unroll
                for (int k = 0; k < 4; k++) {
                    const float4 q1 = __ldcg((const float4*)(g_mod + 4 * 512 + rq * 128 + r0 + k * 4)), q0 = __ldcg((const float4*)(g_mod + 3 * 512 + rq * 128 + r0 + k * 4));
                    m1[4 * k] = q1.x; m1[4 * k + 1] = q1.y; m1[4 * k + 2] = q1.z; m1[4 * k + 3] = q1.w;
                    m0[4 * k] = q0.x; m0[4 * k + 1] = q0.y; m0[4 * k + 2] = q0.z; m0[4 * k + 3] = q0.w;
                }
#pragma unroll
                for (int k = 0; k < 16; k++) {
                    const float f[8] = {bf_lo(v[k].x), bf_hi(v[k].x), bf_lo(v[k].y), bf_hi(v[k].y), bf_lo(v[k].z), bf_hi(v[k].z), bf_lo(v[k].w), bf_hi(v[k].w)};
                    const float c1 = bf_round(1.f + m1[k]);
#pragma unroll
                    for (int e = 0; e < 8; e++) { cs[e] = fmaf(c1, f[e], cs[e]); bi[e] = fmaf(m0[k], f[e], bi[e]); }
                }
            }
#pragma unroll
            for (int e = 0; e < 8; e++) { red[(rq * 2 + 0) * 176 + cg * 8 + e] = cs[e]; red[(rq * 2 + 1) * 176 + cg * 8 + e] = bi[e]; }
        }
        named_bar(3, 128);
        float* outb = (float*)(smem + AX_OUT);
        for (int i = t; i < 352; i += 128) {
            const int row = i / 176, c = i % 176;
            outb[row * 768 + 512 + c] = (red[(0 + row) * 176 + c] + red[(2 + row) * 176 + c]) + (red[(4 + row) * 176 + c] + red[(6 + row) * 176 + c]);
        }
        fence_async_smem();
        named_bar(4, 256);
        return;
    }
    const int wt = tid - 128;
    for (int d = wt; d < 512; d += 128) {
        const float cval = __bfloat162float(p.c[d]);
        aux_put_a(smem, 0, 0, d, __fdividef(cval, 1.f + __expf(-cval)));
    }
    fence_async_smem();
    named_bar(1, 128);
    float* outb = (float*)(smem + AX_OUT);
    int slot = 0; uint32_t ph = 0;
    auto run_group = [&](auto kmaj, int which, int g0) {
        float acc[128];
#pragma unroll
        for (int i = 0; i < 128; i++) acc[i] = 0.f;
        fence_regs(acc);
        int pslot = 0;
#pragma unroll 1
        for (int kb = 0; kb < 8; kb++) {
            mbar_wait(sb + AX_BAR + 8 * slot, ph);
            const uint64_t da = make_desc(sb + AX_A + which * 8192 + kb * 1024, 16, 0);
            const uint64_t db = decltype(kmaj)::value ? make_desc(sb + slot * 32768, 16, 1024) : make_desc(sb + slot * 32768, 8192, 1024);
            wgmma_fence();
#pragma unroll
            for (int k = 0; k < 4; k++) {
                if (decltype(kmaj)::value) wgmma_n256<0>(acc, da + k * 2, db + k * 2, 1);
                else wgmma_n256<1>(acc, da + k * 2, db + k * 128, 1);
            }
            wgmma_commit();
            wgmma_wait<1>();
            if (kb > 0 && wt == 0) mbar_arrive(sb + AX_BAR + 8 * (AX_NS + pslot));
            pslot = slot;
            if (++slot == AX_NS) { slot = 0; ph ^= 1; }
        }
        wgmma_wait<0>();
        fence_regs(acc);
        if (wt == 0) mbar_arrive(sb + AX_BAR + 8 * (AX_NS + pslot));
        if (wt < 8) {
            const int row = wt >> 2, c0 = (wt & 3) * 2;
            if (row == 0 || which == 2) {
#pragma unroll
                for (int i = 0; i < 32; i++) {
                    const int c = g0 + i * 8 + c0;
                    const float v0 = which == 0 ? bf_round(acc[4 * i]) : acc[4 * i], v1 = which == 0 ? bf_round(acc[4 * i + 1]) : acc[4 * i + 1];
                    outb[row * 768 + c] = v0; outb[row * 768 + c + 1] = v1;
                }
            }
        }
    };
#pragma unroll 1
    for (int g = 0; g < 3; g++) run_group(BoolC<false>{}, 0, g * 256);
    {
        fence_async_smem();
        named_bar(1, 128);
        if (wt == 0) {
            bulk_store(g_mod + a * 768, sb + AX_OUT, 3072);
            bulk_commit(); bulk_wait_all();
            cnt_add(CN_MOD); cnt_add(CN_MOD + 1);
            TRACE(51);
            cnt_wait<0>(CN_MOD, tag, NAUX);
        }
        named_bar(1, 128);
        named_bar(2, 256);
        float t[3][4];
#pragma unroll
        for (int k = 0; k < 4; k++) { const int d = wt + 128 * k; t[0][k] = __ldcg(g_mod + d); t[1][k] = __ldcg(g_mod + 4 * 512 + d); t[2][k] = __ldcg(g_mod + 3 * 512 + d); }
#pragma unroll
        for (int k = 0; k < 4; k++) { const int d = wt + 128 * k; aux_put_a(smem, 1, 0, d, t[0][k]); aux_put_a(smem, 2, 0, d, 1.f + t[1][k]); aux_put_a(smem, 2, 1, d, t[2][k]); }
        fence_async_smem();
        named_bar(1, 128);
    }
    run_group(BoolC<true>{}, 1, 0);
    {
        fence_async_smem();
        named_bar(1, 128);
        if (wt == 0) {
            bulk_store(g_v + a * 256, sb + AX_OUT, 1024);
            bulk_commit(); bulk_wait_all();
            cnt_add(CN_V); cnt_add(CN_V + 1);
            TRACE(53);
        }
        named_bar(1, 128);
    }
#pragma unroll 1
    for (int g = 0; g < 2; g++) run_group(BoolC<false>{}, 2, g * 256);
    fence_async_smem();
    named_bar(4, 256);
    if (wt == 0) {
        const int isu = a >> 1, col0 = (a & 1) * 688;
        bulk_store(g_cs + (isu * 2 + 0) * F_ + col0, sb + AX_OUT, 688 * 4);
        bulk_store(g_cs + (isu * 2 + 1) * F_ + col0, sb + AX_OUT + 768 * 4, 688 * 4);
        bulk_commit(); bulk_wait_all();
        cnt_add(CN_CS); cnt_add(CN_CS + 1);
        TRACE(54);
        unsigned old = atomicInc(&g_done, NCTA + NAUX - 1);
        if (old == NCTA + NAUX - 1) g_epoch = tag;
    }
}

__global__ void __launch_bounds__(384, 1) mega_kernel(const __grid_constant__ Params p) {
    extern __shared__ __align__(1024) uint8_t smem_raw[];
    TRACE_INIT();
    const int tid = threadIdx.x;
    const int b = blockIdx.x;
    const int lane = tid & 31;
    uint4 xv[2][2];
    if (tid >= 128 && b < NCTA) {
        const __nv_bfloat16* xr = p.x + (size_t)(b * 16 + ((tid - 128) >> 5) * 2) * D_ + lane * 8;
#pragma unroll
        for (int rr = 0; rr < 2; rr++) { xv[rr][0] = ldg_stream(xr + rr * D_); xv[rr][1] = ldg_stream(xr + rr * D_ + 256); }
    }
    const unsigned tag = ld_relaxed(&g_epoch) + 1;
    const uint32_t sb = smem_u32(smem_raw);
    if (sb & 1023u) __trap();
    if (b >= NCTA) {
        aux_cta(p, smem_raw, sb, b - NCTA, tag, 0);
        return;
    }
    const int warp = __shfl_sync(0xffffffffu, tid >> 5, 0);
    const int rho = b & 1;
    const int rb = b >> 3;
    const int pi = (b >> 1) & 3;
    const int part1 = pi >> 1, nt1 = (pi & 1) * 2 + rho;
    const int j3 = pi * 2 + rho;
    auto slice3 = [&](int kk) { return (j3 + kk) & 7; };
    const int col2 = pi * 128 + rho * 64;

    if (tid == 0) TRACE_GT(0);
    {
        constexpr int NBAR = (SMEM_USED - OFF_BAR) / 8;
        if (elect_one()) {
#pragma unroll 1
            for (int i = warp; i < NBAR; i += 12) {
                uint32_t a = OFF_BAR + 8 * i;
                uint32_t cnt = 1;
                if (a >= BAR_EMPTYB && a < BAR_FULLA) cnt = 2;
                else if (a == BAR_XARR) cnt = 8;
                mbar_init(sb + a, cnt);
            }
            asm volatile("fence.mbarrier_init.release.cluster;" ::: "memory");
        }
    }
    if (warp == 2 && lane < M_COUNT) prefetch_tmap(&p.m[lane]);
    if (warp == 3) {
#pragma unroll
        for (int k = 0; k < 2; k++) asm volatile("st.shared.v4.u32 [%0], {%1, %1, %1, %1};" :: "r"(sb + OFF_ONES + (lane + 32 * k) * 16), "r"(0x3f803f80u) : "memory");
#pragma unroll
        for (int k = 0; k < 2; k++) asm volatile("st.shared.v4.u32 [%0], {%1, %1, %1, %1};" :: "r"(sb + OFF_ZERO + (lane + 32 * k) * 16), "r"(0u) : "memory");
        fence_async_smem();
    }
    const uint32_t peer_sb = mapa(sb, rho ^ 1);
    __syncthreads();
    cluster_arrive();

    if (warp < 4) {
        cluster_wait();
        if (tid == 0) TRACE(33);
        reg_dealloc<72>();
        if (warp == 0) {
            if (elect_one()) {
                cnt_wait<0>(CN_X + ((b >> 1) & 7), tag, 128);
                fence_async_global();
                uint32_t ph = 0x1ff;
                TRACE(1);
                int slot = 0;
#pragma unroll 1
                for (int kb = 0; kb < 32; kb++) {
                    uint32_t full = sb + BAR_FULLB + 8 * slot, dst = sb + OFF_B + slot * 16384;
                    mbar_wait(sb + BAR_EMPTYB + 8 * slot, bit(ph, slot));
                    TRACE2(6, kb);
                    mbar_expect_tx(full, 16384);
                    tma_load(dst, &p.m[M_XN], nt1 * 128, kb * 64, full);
                    tma_load(dst + 8192, &p.m[M_XN], nt1 * 128 + 64, kb * 64, full);
                    if (kb == 4) { bulk_prefetch((const char*)p.dr + (size_t)b * 4096, 4096); bulk_prefetch((const char*)p.di + (size_t)b * 4096, 4096); }
                    if (kb == 10) bulk_prefetch((const char*)p.wg + (size_t)b * 11008, 11008);
                    if (kb == 16) bulk_prefetch((const char*)p.wu + (size_t)b * 11008, 11008);
                    if (kb == 26) bulk_prefetch((const char*)p.wd + (size_t)b * 11008, 11008);
                    ph ^= 1u << slot;
                    if (++slot == NB1) slot = 0;
                }
#pragma unroll 1
                for (int kk = 0; kk < 8; kk++) {
                    slot = (P2_SLOTS >> (4 * kk)) & 15;
                    uint32_t full = sb + BAR_FULLB + 8 * slot, dst = sb + OFF_B + slot * 16384;
                    if (slot >= 7) {
                        mbar_wait(sb + BAR_EMPTYA + 8 * (NA1 * (slot - 7) + 4), 0);
                        mbar_wait(sb + BAR_EMPTYA + 8 * (NA1 * (slot - 7) + 5), 0);
                    } else {
                        mbar_wait(sb + BAR_EMPTYB + 8 * slot, bit(ph, slot));
                    }
                    mbar_expect_tx(full, 16384);
                    const int c = (pi + (kk >> 1)) & 3, kcol = ((c & 1) * 2 + rho) * 128 + (kk & 1) * 64;
                    const CUtensorMap* md = &p.m[(c >> 1) ? M_DI : M_DR];
                    tma_load(dst, md, kcol, col2, full);
                    tma_load(dst + 8192, md, kcol, col2 ^ 64, full);
                    ph ^= 1u << slot;
                }
                slot = 3;
#pragma unroll 1
                for (int kk = 0; kk < 8; kk++) {
                    uint32_t dst = sb + OFF_B + slot * 16384;
                    uint32_t full = sb + BAR_FULLB + 8 * slot;
                    mbar_wait(sb + BAR_EMPTYB + 8 * slot, bit(ph, slot));
                    if (kk < 3) { mbar_wait(sb + BAR_EMPTYB + 8 * (slot + 1), bit(ph, slot + 1)); mbar_wait(sb + BAR_EMPTYB + 8 * (slot + 2), bit(ph, slot + 2)); }
                    mbar_expect_tx(full, 49152);
                    TRACE2(5, 8 + kk);
                    const int krow = slice3(kk) * 64;
#pragma unroll
                    for (int ch = 0; ch < 3; ch++) tma_load(dst + ch * 8192, &p.m[M_WG], j3 * 176 + ch * 64, krow, full);
#pragma unroll
                    for (int ch = 0; ch < 3; ch++) tma_load(dst + (3 + ch) * 8192, &p.m[M_WU], j3 * 176 + ch * 64, krow, full);
                    ph ^= 1u << slot;
                    slot += 3; if (slot == NB) slot = 0;
                }
                slot = 0;
                const uint32_t ph0 = ph;
#pragma unroll 1
                for (int t = 0; t < 12; t++) {
                    uint32_t full = sb + BAR_FULLB + 8 * slot, dst = sb + OFF_B + slot * 16384;
                    if (t < NB && slot % 3 != 0) { const int g0 = slot - slot % 3; mbar_wait(sb + BAR_EMPTYB + 8 * g0, bit(ph0, g0)); }
                    else mbar_wait(sb + BAR_EMPTYB + 8 * slot, bit(ph, slot));
                    mbar_expect_tx(full, 16384);
                    const int krow = (((pi + t / 3) & 3) * 2 + rho) * 176 + (t % 3) * 64;
                    tma_load(dst, &p.m[M_WD], col2, krow, full);
                    tma_load(dst + 8192, &p.m[M_WD], col2 ^ 64, krow, full);
                    ph ^= 1u << slot;
                    if (++slot == NB) slot = 0;
                }
            }
        } else if (warp <= 2) {
            const int w = warp - 1;
            const uint32_t fullb = sb + BAR_FULLA + 8 * NA1 * w, emptyb = sb + BAR_EMPTYA + 8 * NA1 * w;
            const uint32_t pemptyb = sb + BAR_PEMPTYA + 8 * NA1 * w;
            const uint32_t abase = sb + OFF_A + w * (NA * 8192), stg = sb + BAR_STG + 16 * w;
            const int row0 = rb * 128 + w * 64;
            if (elect_one()) {
                uint32_t ph = 0x3f;
                const CUtensorMap* ma = &p.m[part1 ? M_WIM : M_WRE];
                int slot = 0, lap = 0;
                mbar_wait(sb + BAR_XARR, 0);
#pragma unroll 1
                for (int m = 0; m < 32; m++) {
                    mbar_wait(emptyb + 8 * slot, bit(ph, slot));
                    mbar_expect_tx(fullb + 8 * slot, 8192);
                    if ((m & 1) == rho) {
                        if (lap > 0) mbar_wait(pemptyb + 8 * slot, (lap - 1) & 1);
                        tma_load_mc(a_slot_addr(sb, w, slot), ma, m * 64, row0, fullb + 8 * slot);
                    }
                    if (w == 0) TRACE2(3, m);
                    ph ^= 1u << slot;
                    if (++slot == NA1) { slot = 0; lap++; }
                }
                auto load_a = [&](int sl, auto&& issue) {
                    mbar_wait(emptyb + 8 * sl, bit(ph, sl));
                    mbar_expect_tx(fullb + 8 * sl, 8192);
                    issue(abase + sl * 8192, fullb + 8 * sl);
                    ph ^= 1u << sl;
                };
                mbar_wait(stg, 0);
                tma_store(&p.m[M_PQ], abase + 2 * 8192, part1 * 512 + nt1 * 128, row0); bulk_commit();
                mbar_wait(stg + 8, 0);
                tma_store(&p.m[M_PQ], abase + 3 * 8192, part1 * 512 + nt1 * 128 + 64, row0);
                bulk_store(g_rs + ((part1 * 16 + rb) * 4 + nt1) * 128 + w * 64, sb + OFF_RSP + w * 256, 256);
                bulk_commit();
                if (w == 0) TRACE(43);
                bulk_wait_all();
                cnt_add(CN_1 + (rb * 2 + rho) * 2 + w);
                if (w == 0) TRACE(8);
                cnt_wait<0>(CN_1 + (rb * 2 + rho) * 2 + w, tag, 4);
                if (w == 0) TRACE(56);
                fence_async_global();
#pragma unroll 1
                for (int kk = 2; kk < 8; kk++) {
                    const int c = (pi + (kk >> 1)) & 3, col = (c >> 1) * 512 + ((c & 1) * 2 + rho) * 128 + (kk & 1) * 64;
                    load_a((kk - 2) & 3, [&](uint32_t dst, uint32_t bar) { tma_load(dst, &p.m[M_PQ], col, row0, bar); });
                }
                if (w == 0) TRACE(2);
                mbar_wait(stg, 1);
                tma_store(&p.m[M_Z], abase + 3 * 8192, col2, row0); bulk_commit();
                bulk_wait_all();
                cnt_add(CN_2 + rb * 2 + w);
                if (w == 0) TRACE(11);
                mbar_wait(stg + 8, 1);
                bulk_store(g_stats + ((rb * 2 + w) * 8 + j3) * 64, sb + OFF_ST + w * 512, 512); bulk_commit();
                cnt_wait<0>(CN_2 + rb * 2 + w, tag, 8);
                if (w == 0) TRACE(57);
                fence_async_global();
#pragma unroll 1
                for (int kk = 1; kk < 8; kk++) {
                    const int sl = (kk - 1) & 3;
                    load_a(sl, [&](uint32_t dst, uint32_t bar) { tma_load(dst, &p.m[M_Z], slice3(kk) * 64, row0, bar); });
                    if (kk == 2) { bulk_wait_all(); cnt_add(CN_2S + rb * 2 + w); }
                    if (kk == 3) { cnt_wait<0>(CN_2S + rb * 2 + w, tag, 8); mbar_arrive(sb + BAR_DEP + 8 * w); }
                }
                if (w == 0) TRACE(3);
                uint8_t* hdst = g_h + (size_t)((rb * 2 + w) * 8 + j3) * 3 * 8192;
                mbar_wait(stg, 0); bulk_store(hdst, abase + 3 * 8192, 8192); bulk_commit();
                mbar_wait(stg + 8, 0); bulk_store(hdst + 8192, abase + 0 * 8192, 8192); bulk_commit();
                mbar_wait(stg, 1); bulk_store(hdst + 16384, abase + 1 * 8192, 8192); bulk_commit();
                bulk_wait_all();
                cnt_add(CN_3 + (rb * 2 + rho) * 2 + w);
                if (w == 0) TRACE(14);
                cnt_wait<0>(CN_3 + (rb * 2 + rho) * 2 + w, tag, 4);
                if (w == 0) TRACE(58);
                fence_async_global();
#pragma unroll 1
                for (int t = 3; t < 12; t++) {
                    const int jj = ((pi + t / 3) & 3) * 2 + rho;
                    const uint8_t* src = g_h + (size_t)(((rb * 2 + w) * 8 + jj) * 3 + t % 3) * 8192;
                    load_a((t - 1) & 3, [&](uint32_t dst, uint32_t bar) { bulk_load(dst, src, 8192, bar); });
                }
                if (w == 0) TRACE(4);
                mbar_wait(stg + 8, 1);
                tma_store(&p.m[M_OUT], abase, col2, row0); bulk_commit();
                asm volatile("cp.async.bulk.wait_group.read 0;" ::: "memory");
                if (w == 0) TRACE(17);
            }
        } else {
            if (lane == 0) cnt_wait<300>(CN_MOD + (b & 1), tag, NAUX);
            __syncwarp();
            {
                const float* md = g_mod;
                float t0[4], t1[6];
#pragma unroll
                for (int k = 0; k < 4; k++) t0[k] = __ldcg(md + 1 * 512 + nt1 * 128 + lane + 32 * k);
#pragma unroll
                for (int k = 0; k < 2; k++) {
                    const int col = col2 + lane + 32 * k;
                    t1[3 * k] = __ldcg(md + 2 * 512 + col); t1[3 * k + 1] = __ldcg(md + 4 * 512 + col); t1[3 * k + 2] = __ldcg(md + 5 * 512 + col);
                }
#pragma unroll
                for (int k = 0; k < 4; k++) sts_f(sb + OFF_CA1 + (lane + 32 * k) * 4, (part1 ? -1.f : 1.f) * bf_round(1.f + t0[k]));
#pragma unroll
                for (int k = 0; k < 2; k++) {
                    sts_f(sb + OFF_GA + (lane + 32 * k) * 4, t1[3 * k]); sts_f(sb + OFF_CB1 + (lane + 32 * k) * 4, bf_round(1.f + t1[3 * k + 1])); sts_f(sb + OFF_GB + (lane + 32 * k) * 4, t1[3 * k + 2]);
                }
                __syncwarp();
                if (lane == 0) { mbar_arrive(sb + BAR_AUX); TRACE(52); }
            }
            if (lane == 0) cnt_wait<300>(CN_V + (b & 1), tag, NAUX);
            __syncwarp();
            {
                float tr[4], ti[4];
#pragma unroll
                for (int k = 0; k < 4; k++) {
                    const int cidx = lane + 32 * k, col = (col2 ^ (cidx & 64)) + (cidx & 63);
                    tr[k] = __ldcg(g_v + col); ti[k] = __ldcg(g_v + 512 + col);
                }
#pragma unroll
                for (int k = 0; k < 4; k++) {
                    uint32_t rh, rl, ih, il;
                    split_bf16(tr[k], rh, rl); split_bf16(-ti[k], ih, il);
                    sts_u4(sb + OFF_SA + (lane + 32 * k) * 16, make_uint4(rh | (rl << 16), rh | (rl << 16), ih | (il << 16), ih | (il << 16)));
                }
                fence_async_smem();
                __syncwarp();
                if (lane == 0) { mbar_arrive(sb + BAR_AUX + 8); TRACE(53); }
            }
            if (lane == 0) cnt_wait<300>(CN_CS + (b & 1), tag, NAUX);
            __syncwarp();
            {
                float t[6][4];
#pragma unroll
                for (int k = 0; k < 6; k++) {
                    const int cidx = lane + 32 * k, f = j3 * 176 + cidx;
                    const bool ok = cidx < 176 && f < F_;
#pragma unroll
                    for (int q = 0; q < 4; q++) t[k][q] = ok ? __ldcg(g_cs + q * F_ + f) : 0.f;
                }
#pragma unroll
                for (int k = 0; k < 6; k++) {
                    const int cidx = lane + 32 * k;
                    if (cidx < 176) {
#pragma unroll
                        for (int m = 0; m < 2; m++) {
                            uint32_t ch, cl, bh, bl;
                            split_bf16(t[k][2 * m], ch, cl); split_bf16(t[k][2 * m + 1], bh, bl);
                            const uint32_t cw2 = ch | (cl << 16), bw2 = bh | (bl << 16);
                            sts_u4(sb + OFF_BX + (m * 176 + cidx) * 16, make_uint4(cw2, cw2, bw2, bw2));
                        }
                    }
                }
                fence_async_smem();
            }
            __syncwarp();
            if (lane == 0) { mbar_arrive(sb + BAR_AUX + 16); TRACE(50); }
        }
        __syncwarp();
        cluster_arrive();
        cluster_wait();
    } else {
        const int ct = tid - 128;
        const int w = (warp >> 2) - 1;
        const int wt = ct & 127;
        const int cw = warp - 4;
        {
            float f[2][16];
#pragma unroll
            for (int rr = 0; rr < 2; rr++) {
                const uint32_t u[8] = {xv[rr][0].x, xv[rr][0].y, xv[rr][0].z, xv[rr][0].w, xv[rr][1].x, xv[rr][1].y, xv[rr][1].z, xv[rr][1].w};
#pragma unroll
                for (int k = 0; k < 8; k++) { f[rr][2 * k] = bf_lo(u[k]); f[rr][2 * k + 1] = bf_hi(u[k]); }
            }
            float s0 = 0.f, s1 = 0.f;
#pragma unroll
            for (int k = 0; k < 16; k++) { s0 += f[0][k]; s1 += f[1][k]; }
#pragma unroll
            for (int o = 16; o > 0; o >>= 1) { s0 += __shfl_xor_sync(0xffffffffu, s0, o); s1 += __shfl_xor_sync(0xffffffffu, s1, o); }
            if (ct == 0) TRACE(24);
            if (lane == 0) mbar_arrive(sb + BAR_XARR);
            s0 *= (1.f / 512.f); s1 *= (1.f / 512.f);
            float v0 = 0.f, v1 = 0.f;
#pragma unroll
            for (int k = 0; k < 16; k++) { f[0][k] -= s0; v0 = fmaf(f[0][k], f[0][k], v0); f[1][k] -= s1; v1 = fmaf(f[1][k], f[1][k], v1); }
#pragma unroll
            for (int o = 16; o > 0; o >>= 1) { v0 += __shfl_xor_sync(0xffffffffu, v0, o); v1 += __shfl_xor_sync(0xffffffffu, v1, o); }
            const float rstd[2] = {rsqrtf(v0 * (1.f / 512.f) + 1e-5f), rsqrtf(v1 * (1.f / 512.f) + 1e-5f)};
            const uint32_t stg = sb + OFF_B + cw * 2048 + lane * 16;
#pragma unroll
            for (int rr = 0; rr < 2; rr++) {
                uint32_t o[8];
#pragma unroll
                for (int k = 0; k < 8; k++) o[k] = pack_bf16(f[rr][2 * k] * rstd[rr], f[rr][2 * k + 1] * rstd[rr]);
                sts_u4(stg + rr * 1024, make_uint4(o[0], o[1], o[2], o[3]));
                sts_u4(stg + rr * 1024 + 512, make_uint4(o[4], o[5], o[6], o[7]));
            }
            fence_async_smem();
            __syncwarp();
            if (elect_one()) {
                bulk_store(g_xn + (size_t)(b * 16 + cw * 2) * D_, sb + OFF_B + cw * 2048, 2048);
                bulk_commit();
                bulk_wait_all();
            }
            __syncwarp();
            if (ct == 0) TRACE(31);
            named_bar(1, 256);
            if (ct < 8) cnt_add(CN_X + ct);
            if (ct == 0) TRACE(5);
            cluster_wait();
        }
        reg_alloc<216>();
        const int cwarp = warp & 3;
        const int r0 = cwarp * 16 + (lane >> 2);
        const int c0 = (lane & 3) * 2;
        const uint32_t abase = sb + OFF_A + w * (NA * 8192);
        const uint32_t fullA = sb + BAR_FULLA + 8 * NA1 * w, emptyA = sb + BAR_EMPTYA + 8 * NA1 * w;
        const uint32_t peer_pemptyA = peer_sb + BAR_PEMPTYA + 8 * NA1 * w;
        const uint32_t fullB = sb + BAR_FULLB, emptyB = sb + BAR_EMPTYB, stgb = sb + BAR_STG + 16 * w;
        const int sm_row = cwarp * 16 + (lane & 7) + ((lane >> 3) & 1) * 8;
        const int sm_cg = lane >> 4;
        const uint32_t sm_off = sm_row * 128, sm_sw = sm_row & 7;
        uint32_t pha = 0, phb = 0;
        uint32_t stg_ev = 0;
        auto staged = [&]() { fence_async_smem(); named_bar(2 + w, 128); if (wt == 0) mbar_arrive(stgb + 8 * (stg_ev & 1)); stg_ev++; };

        {
            float acc[64];
#pragma unroll
            for (int i = 0; i < 64; i++) acc[i] = 0.f;
            fence_regs(acc);
            float rsacc[4] = {0.f, 0.f, 0.f, 0.f};
            fence_regs(rsacc);
            const uint64_t d_ones = make_desc(sb + OFF_ONES, 16, 1024);
            int sa = 0, sbb = 0, psa = 0, psb = 0, kb = 0;
            auto step = [&](auto own) {
                mbar_wait(fullA + 8 * sa, bit(pha, sa));
                if (ct == 0) TRACE2(0, kb);
                mbar_wait(fullB + 8 * sbb, bit(phb, sbb));
                if (kb == 0 && ct == 0) TRACE(6);
                uint64_t da = make_desc(a_slot_addr(sb, w, sa), 16, 1024);
                uint64_t db = make_desc(sb + OFF_B + sbb * 16384, 8192, 1024);
                wgmma_fence();
#pragma unroll
                for (int k = 0; k < 4; k++) wgmma_n128<1>(acc, da + k * 2, db + k * 128, 1);
                if (decltype(own)::value) {
#pragma unroll
                    for (int k = 0; k < 4; k++) wgmma_n8<0>(rsacc, da + k * 2, d_ones, 1);
                }
                wgmma_commit();
                wgmma_wait<1>();
                if (kb > 0 && wt == 0) {
                    if (kb - 1 + NA1 < 32 && ((kb - 1) & 1) != rho) mbar_arrive_cl(peer_pemptyA + 8 * psa);
                    if (kb != 27 && kb != 28) mbar_arrive(emptyA + 8 * psa);
                    mbar_arrive(emptyB + 8 * psb);
                }
                pha ^= 1u << sa; phb ^= 1u << sbb;
                psa = sa; psb = sbb;
                if (++sa == NA1) sa = 0;
                if (++sbb == NB1) sbb = 0;
                kb++;
            };
            using Yes = BoolC<true>; using No = BoolC<false>;
#pragma unroll 1
            for (int i = 0; i < nt1; i++) step(No{});
#pragma unroll 1
            for (int g = 0; g < 7; g++) { step(Yes{}); step(No{}); step(No{}); step(No{}); }
            step(Yes{});
#pragma unroll 1
            for (int i = nt1; i < 3; i++) step(No{});
            wgmma_wait<0>();
            fence_regs(acc);
            if (wt == 0) { mbar_arrive(emptyB + 8 * 3); mbar_arrive(emptyA + 8 * 1); }
            if (ct == 0) TRACE(7);
            PROG(10);
            fence_regs(rsacc);
            if ((lane & 3) == 0) { sts_f(sb + OFF_RSP + (w * 64 + r0) * 4, rsacc[0]); sts_f(sb + OFF_RSP + (w * 64 + r0 + 8) * 4, rsacc[2]); }
            mbar_wait(sb + BAR_AUX, 0);
            const float2* ca1 = (const float2*)(smem_raw + OFF_CA1) + (lane & 3);
#pragma unroll
            for (int hf = 0; hf < 2; hf++) {
#pragma unroll
                for (int i = hf * 8; i < hf * 8 + 8; i += 2) {
                    const float2 c0v = ca1[i * 4], c1v = ca1[i * 4 + 4];
                    const float* a = &acc[i * 4];
                    const int cg = (i & 7) + sm_cg;
                    stsm4(abase + (2 + hf) * 8192 + sm_off + ((cg ^ sm_sw) << 4),
                          pack_bf16(a[0] * c0v.x, a[1] * c0v.y), pack_bf16(a[2] * c0v.x, a[3] * c0v.y), pack_bf16(a[4] * c1v.x, a[5] * c1v.y), pack_bf16(a[6] * c1v.x, a[7] * c1v.y));
                }
                staged();
            }
            if (ct == 0) TRACE(41);
            PROG(11);
        }
        {
            uint32_t xr[16];
            {
                const __nv_bfloat16* xp = p.x + (size_t)(rb * 128 + w * 64 + r0) * D_ + col2 + c0;
#pragma unroll
                for (int i = 0; i < 8; i++) {
                    xr[2 * i] = __ldg((const uint32_t*)(xp + i * 8));
                    xr[2 * i + 1] = __ldg((const uint32_t*)(xp + 8 * D_ + i * 8));
                }
            }
            float acc[64];
#pragma unroll
            for (int i = 0; i < 64; i++) acc[i] = 0.f;
            fence_regs(acc);
            float rpa[4], rpb[4];
            int psb = 0;
#pragma unroll 1
            for (int kk = 0; kk < 8; kk++) {
                const int sa = (kk + 2) & 3, sbb = (P2_SLOTS >> (4 * kk)) & 15;
                if (kk >= 2) { mbar_wait(fullA + 8 * sa, bit(pha, sa)); pha ^= 1u << sa; }
                mbar_wait(fullB + 8 * sbb, bit(phb, sbb));
                if (kk == 2 && ct == 0) TRACE(9);
                if (ct == 0) TRACE2(4, kk);
                PROG(20 + kk);
                if (kk == 2) {
#pragma unroll
                    for (int c = 0; c < 4; c++) {
                        const float* rp = g_rs + (((c >> 1) * 16 + rb) * 4 + (c & 1) * 2 + rho) * 128 + w * 64 + r0;
                        rpa[c] = __ldcg(rp); rpb[c] = __ldcg(rp + 8);
                    }
                }
                uint64_t da = make_desc(abase + sa * 8192, 16, 1024);
                uint64_t db = make_desc(sb + OFF_B + sbb * 16384, 16, 1024);
                wgmma_fence();
#pragma unroll
                for (int k = 0; k < 4; k++) wgmma_n128<0>(acc, da + k * 2, db + k * 2, 1);
                wgmma_commit();
                if (kk == 6) {
                    if ((lane & 3) < 2) {
                        const bool second = lane & 1;
                        uint32_t rh, rl, ih, il;
                        split_bf16(second ? rpb[0] + rpb[1] : rpa[0] + rpa[1], rh, rl); split_bf16(second ? rpb[2] + rpb[3] : rpa[2] + rpa[3], ih, il);
                        sts_u4(sb + OFF_AX + w * 1024 + (r0 + (second ? 8 : 0)) * 16, make_uint4(rh | (rh << 16), rl | (rl << 16), ih | (ih << 16), il | (il << 16)));
                    }
                    fence_async_smem();
                }
                wgmma_wait<1>();
                if (kk > 0 && wt == 0) {
                    if (kk - 1 < 4 || kk - 1 == 6) mbar_arrive(emptyA + 8 * ((kk + 1) & 3));
                    if (kk == 5) { mbar_expect_tx(sb + BAR_RFULL + 8 * w, 8192); mbar_arrive_cl(peer_sb + BAR_PRDY + 8 * w); }
                    mbar_arrive(emptyB + 8 * psb);
                }
                phb ^= 1u << sbb;
                psb = sbb;
            }
            {
                named_bar(2 + w, 128);
                mbar_wait(sb + BAR_AUX + 8, 0);
                wgmma_fence();
                wgmma_n128<0>(acc, make_desc_ns(sb + OFF_AX + w * 1024, OFF_ZERO - (OFF_AX + w * 1024), 128), make_desc_ns(sb + OFF_SA, 0, 128), 1);
                wgmma_commit();
            }
            wgmma_wait<0>();
            fence_regs(acc);
            if (wt == 0) { mbar_arrive(emptyB + 8 * psb); mbar_arrive(emptyA + 8 * 1); }
            if (ct == 0) TRACE(10);
            PROG(30);
            {
                uint32_t snd[16];
#pragma unroll
                for (int j = 0; j < 16; j++) snd[j] = pack_bf16(acc[32 + 2 * j], acc[33 + 2 * j]);
                mbar_wait(sb + BAR_PRDY + 8 * w, 0);
                const uint32_t rdst = peer_sb + OFF_A + w * (NA * 8192) + 2 * 8192 + wt * 16, rbar = peer_sb + BAR_RFULL + 8 * w;
#pragma unroll
                for (int j = 0; j < 4; j++) st_async4u(rdst + j * 2048, snd[4 * j], snd[4 * j + 1], snd[4 * j + 2], snd[4 * j + 3], rbar);
            }
            const float2* gap = (const float2*)(smem_raw + OFF_GA) + (lane & 3);
            const float2* cbp = (const float2*)(smem_raw + OFF_CB1) + (lane & 3);
            mbar_wait_cl(sb + BAR_RFULL + 8 * w, 0);
            if (ct == 0) TRACE(45);
            PROG(31);
            float s0 = 0.f, s1 = 0.f;
            uint32_t x2p[16];
            {
                uint32_t rcv[16], zz[16];
#pragma unroll
                for (int j = 0; j < 4; j++) { const uint4 r = lds_u4(abase + 2 * 8192 + j * 2048 + wt * 16); rcv[4 * j] = r.x; rcv[4 * j + 1] = r.y; rcv[4 * j + 2] = r.z; rcv[4 * j + 3] = r.w; }
#pragma unroll
                for (int j = 0; j < 8; j++) {
                    const float2 ga = gap[j * 4], cb = cbp[j * 4];
                    const float v0 = fmaf(ga.x, acc[4 * j] + bf_lo(rcv[2 * j]), bf_lo(xr[2 * j])), v1 = fmaf(ga.y, acc[4 * j + 1] + bf_hi(rcv[2 * j]), bf_hi(xr[2 * j]));
                    const float v2 = fmaf(ga.x, acc[4 * j + 2] + bf_lo(rcv[2 * j + 1]), bf_lo(xr[2 * j + 1])), v3 = fmaf(ga.y, acc[4 * j + 3] + bf_hi(rcv[2 * j + 1]), bf_hi(xr[2 * j + 1]));
                    x2p[2 * j] = pack_bf16(v0, v1); x2p[2 * j + 1] = pack_bf16(v2, v3);
                    acc[4 * j] = bf_lo(x2p[2 * j]); acc[4 * j + 1] = bf_hi(x2p[2 * j]);
                    acc[4 * j + 2] = bf_lo(x2p[2 * j + 1]); acc[4 * j + 3] = bf_hi(x2p[2 * j + 1]);
                    s0 += acc[4 * j] + acc[4 * j + 1]; s1 += acc[4 * j + 2] + acc[4 * j + 3];
                    zz[2 * j] = pack_bf16(acc[4 * j] * cb.x, acc[4 * j + 1] * cb.y);
                    zz[2 * j + 1] = pack_bf16(acc[4 * j + 2] * cb.x, acc[4 * j + 3] * cb.y);
                }
#pragma unroll
                for (int j = 0; j < 8; j += 2) {
                    const int cg = j + sm_cg;
                    stsm4(abase + 3 * 8192 + sm_off + ((cg ^ sm_sw) << 4), zz[2 * j], zz[2 * j + 1], zz[2 * j + 2], zz[2 * j + 3]);
                }
            }
            staged();
            if (wt == 0) mbar_arrive(emptyA + 8 * 2);
            s0 += __shfl_xor_sync(0xffffffffu, s0, 1); s1 += __shfl_xor_sync(0xffffffffu, s1, 1);
            s0 += __shfl_xor_sync(0xffffffffu, s0, 2); s1 += __shfl_xor_sync(0xffffffffu, s1, 2);
            float m0 = s0 * (1.f / 64.f), m1 = s1 * (1.f / 64.f), q0 = 0.f, q1 = 0.f;
#pragma unroll
            for (int j = 0; j < 8; j++) {
                float d0 = acc[4 * j] - m0, d1 = acc[4 * j + 1] - m0, d2 = acc[4 * j + 2] - m1, d3 = acc[4 * j + 3] - m1;
                q0 += d0 * d0 + d1 * d1; q1 += d2 * d2 + d3 * d3;
            }
            q0 += __shfl_xor_sync(0xffffffffu, q0, 1); q1 += __shfl_xor_sync(0xffffffffu, q1, 1);
            q0 += __shfl_xor_sync(0xffffffffu, q0, 2); q1 += __shfl_xor_sync(0xffffffffu, q1, 2);
            if ((lane & 3) == 0) {
                sts_f2(sb + OFF_ST + w * 512 + r0 * 8, m0, q0);
                sts_f2(sb + OFF_ST + w * 512 + (r0 + 8) * 8, m1, q1);
            }
            staged();
            uint4* xs = g_x2s + (size_t)(b * 2 + w) * 512 + wt;
#pragma unroll
            for (int j = 0; j < 4; j++) xs[j * 128] = make_uint4(x2p[4 * j], x2p[4 * j + 1], x2p[4 * j + 2], x2p[4 * j + 3]);
        }
        {
            float ag[88], au[88];
#pragma unroll
            for (int i = 0; i < 88; i++) { ag[i] = 0.f; au[i] = 0.f; }
            fence_regs(ag); fence_regs(au);
            float hg0 = 0.f, hg1 = 0.f;
            float2 st00, st01, st10, st11;
            int sbb = 3, psb = 0;
#pragma unroll 1
            for (int kk = 0; kk < 8; kk++) {
                const int sa = (kk + 3) & 3;
                if (kk >= 1) { mbar_wait(fullA + 8 * sa, bit(pha, sa)); pha ^= 1u << sa; }
                mbar_wait(fullB + 8 * sbb, bit(phb, sbb));
                if (kk == 1 && ct == 0) TRACE(12);
                if (ct == 0) TRACE2(4, 8 + kk);
                PROG(40 + kk);
                if (kk == 4) {
                    mbar_wait(sb + BAR_DEP + 8 * w, 0);
                    const float2* sp = g_stats + (size_t)((rb * 2 + w) * 8 + (lane & 3) * 2) * 64 + r0;
                    st00 = __ldcg(sp); st01 = __ldcg(sp + 64); st10 = __ldcg(sp + 8); st11 = __ldcg(sp + 72);
                }
                uint64_t da = make_desc(abase + sa * 8192, 16, 1024);
                uint64_t dg = make_desc(sb + OFF_B + sbb * 16384, 8192, 1024);
                uint64_t du = make_desc(sb + OFF_B + sbb * 16384 + 3 * 8192, 8192, 1024);
                wgmma_fence();
#pragma unroll
                for (int k = 0; k < 4; k++) {
                    wgmma_n176<1>(ag, da + k * 2, dg + k * 128, 1);
                    wgmma_n176<1>(au, da + k * 2, du + k * 128, 1);
                }
                wgmma_commit();
                if (kk == 6) {
                    float mu0 = st00.x + st01.x, mu1 = st10.x + st11.x;
                    mu0 += __shfl_xor_sync(0xffffffffu, mu0, 1); mu1 += __shfl_xor_sync(0xffffffffu, mu1, 1);
                    mu0 += __shfl_xor_sync(0xffffffffu, mu0, 2); mu1 += __shfl_xor_sync(0xffffffffu, mu1, 2);
                    mu0 *= 0.125f; mu1 *= 0.125f;
                    const float e0 = st00.x - mu0, e1 = st01.x - mu0, e2 = st10.x - mu1, e3 = st11.x - mu1;
                    float v0 = st00.y + st01.y + 64.f * (e0 * e0 + e1 * e1), v1 = st10.y + st11.y + 64.f * (e2 * e2 + e3 * e3);
                    v0 += __shfl_xor_sync(0xffffffffu, v0, 1); v1 += __shfl_xor_sync(0xffffffffu, v1, 1);
                    v0 += __shfl_xor_sync(0xffffffffu, v0, 2); v1 += __shfl_xor_sync(0xffffffffu, v1, 2);
                    v0 = v0 * (1.f / 512.f) + 1e-5f; v1 = v1 * (1.f / 512.f) + 1e-5f;
                    const float rs0 = rsqrtf(v0), rs1 = rsqrtf(v1);
                    hg0 = 0.5f * rs0; hg1 = 0.5f * rs1;
                    if ((lane & 3) < 2) {
                        const bool second = lane & 1;
                        uint32_t mh, ml, sh, sl2;
                        split_bf16(second ? -mu1 : -mu0, mh, ml); split_bf16(second ? v1 * rs1 : v0 * rs0, sh, sl2);
                        sts_u4(sb + OFF_AX + w * 1024 + (r0 + (second ? 8 : 0)) * 16, make_uint4(mh | (mh << 16), ml | (ml << 16), sh | (sh << 16), sl2 | (sl2 << 16)));
                    }
                    fence_async_smem();
                }
                wgmma_wait<1>();
                if (kk > 0 && wt == 0) {
                    if (kk - 1 < 4) mbar_arrive(emptyA + 8 * ((kk + 2) & 3));
                    mbar_arrive(emptyB + 8 * psb);
                }
                phb ^= 1u << sbb;
                psb = sbb;
                sbb += 3; if (sbb == NB) sbb = 0;
            }
            {
                named_bar(2 + w, 128);
                mbar_wait(sb + BAR_AUX + 16, 0);
                const uint64_t dax = make_desc_ns(sb + OFF_AX + w * 1024, OFF_ZERO - (OFF_AX + w * 1024), 128);
                wgmma_fence();
                wgmma_n176<0>(ag, dax, make_desc_ns(sb + OFF_BX, 0, 128), 1);
                wgmma_n176<0>(au, dax, make_desc_ns(sb + OFF_BX + 176 * 16, 0, 128), 1);
                wgmma_commit();
            }
            wgmma_wait<0>();
            fence_regs(ag); fence_regs(au);
            if (wt == 0) { mbar_arrive(emptyB + 8 * psb); mbar_arrive(emptyA + 8 * 2); }
            if (ct == 0) TRACE(13);
            PROG(50);
            auto piece = [&](auto pcc) {
                constexpr int PC = decltype(pcc)::value;
                constexpr int I0 = PC * 8, I1 = PC < 2 ? PC * 8 + 8 : 22;
                constexpr int SLOT = (PC + 3) & 3;
#pragma unroll
                for (int i = I0; i < I1; i += 2) {
                    uint32_t rr[4];
#pragma unroll
                    for (int u = 0; u < 2; u++) {
                        const float* g = &ag[(i + u) * 4];
                        const float* uu = &au[(i + u) * 4];
                        const float h0 = fmaf(tanh_fast(hg0 * g[0]), hg0, hg0) * uu[0], h1 = fmaf(tanh_fast(hg0 * g[1]), hg0, hg0) * uu[1];
                        const float h2 = fmaf(tanh_fast(hg1 * g[2]), hg1, hg1) * uu[2], h3 = fmaf(tanh_fast(hg1 * g[3]), hg1, hg1) * uu[3];
                        rr[u * 2] = pack_bf16(h0, h1); rr[u * 2 + 1] = pack_bf16(h2, h3);
                    }
                    const int cg = (i & 7) + sm_cg;
                    stsm4(abase + SLOT * 8192 + sm_off + ((cg ^ sm_sw) << 4), rr[0], rr[1], rr[2], rr[3]);
                }
                staged();
            };
            piece(IntC<0>{}); piece(IntC<1>{}); piece(IntC<2>{});
            if (ct == 0) TRACE(47);
        }
        {
            uint4 xs4[4];
            {
                const uint4* xs = g_x2s + (size_t)(b * 2 + w) * 512 + wt;
#pragma unroll
                for (int j = 0; j < 4; j++) xs4[j] = __ldcg(xs + j * 128);
            }
            float acc[64];
#pragma unroll
            for (int i = 0; i < 64; i++) acc[i] = 0.f;
            fence_regs(acc);
            int sbb = 0, psb = 0, t = 0;
            auto step = [&](auto nk) {
                const int sa = (t + 3) & 3;
                if (t >= 3) { mbar_wait(fullA + 8 * sa, bit(pha, sa)); pha ^= 1u << sa; }
                mbar_wait(fullB + 8 * sbb, bit(phb, sbb));
                if (t == 3 && ct == 0) TRACE(15);
                if (ct == 0) TRACE2(4, 16 + t);
                PROG(60 + t);
                uint64_t da = make_desc(abase + sa * 8192, 16, 1024);
                uint64_t db = make_desc(sb + OFF_B + sbb * 16384, 8192, 1024);
                wgmma_fence();
#pragma unroll
                for (int k = 0; k < decltype(nk)::value; k++) wgmma_n128<1>(acc, da + k * 2, db + k * 128, 1);
                wgmma_commit();
                wgmma_wait<1>();
                if (t > 0 && wt == 0) {
                    if (t - 1 < 8) mbar_arrive(emptyA + 8 * ((t + 2) & 3));
                    if (t == 9) { mbar_expect_tx(sb + BAR_RFULL + 8 * w, 8192); mbar_arrive_cl(peer_sb + BAR_PRDY + 8 * w); }
                    mbar_arrive(emptyB + 8 * psb);
                }
                phb ^= 1u << sbb;
                psb = sbb;
                if (++sbb == NB) sbb = 0;
                t++;
            };
#pragma unroll 1
            for (int blk = 0; blk < 4; blk++) { step(IntC<4>{}); step(IntC<4>{}); step(IntC<3>{}); }
            wgmma_wait<0>();
            fence_regs(acc);
            if (ct == 0) TRACE(16);
            {
                uint32_t snd[16];
#pragma unroll
                for (int j = 0; j < 16; j++) snd[j] = pack_bf16(acc[32 + 2 * j], acc[33 + 2 * j]);
                mbar_wait(sb + BAR_PRDY + 8 * w, 1);
                const uint32_t rdst = peer_sb + OFF_A + w * (NA * 8192) + 3 * 8192 + wt * 16, rbar = peer_sb + BAR_RFULL + 8 * w;
#pragma unroll
                for (int j = 0; j < 4; j++) st_async4u(rdst + j * 2048, snd[4 * j], snd[4 * j + 1], snd[4 * j + 2], snd[4 * j + 3], rbar);
            }
            const float2* gbp = (const float2*)(smem_raw + OFF_GB) + (lane & 3);
            mbar_wait_cl(sb + BAR_RFULL + 8 * w, 1);
            const uint32_t xp[16] = {xs4[0].x, xs4[0].y, xs4[0].z, xs4[0].w, xs4[1].x, xs4[1].y, xs4[1].z, xs4[1].w,
                                     xs4[2].x, xs4[2].y, xs4[2].z, xs4[2].w, xs4[3].x, xs4[3].y, xs4[3].z, xs4[3].w};
            uint32_t oo[16];
            {
                uint32_t rcv[16];
#pragma unroll
                for (int j = 0; j < 4; j++) { const uint4 r = lds_u4(abase + 3 * 8192 + j * 2048 + wt * 16); rcv[4 * j] = r.x; rcv[4 * j + 1] = r.y; rcv[4 * j + 2] = r.z; rcv[4 * j + 3] = r.w; }
#pragma unroll
                for (int j = 0; j < 8; j++) {
                    const float2 gb = gbp[j * 4];
                    oo[2 * j] = pack_bf16(fmaf(gb.x, acc[4 * j] + bf_lo(rcv[2 * j]), bf_lo(xp[2 * j])), fmaf(gb.y, acc[4 * j + 1] + bf_hi(rcv[2 * j]), bf_hi(xp[2 * j])));
                    oo[2 * j + 1] = pack_bf16(fmaf(gb.x, acc[4 * j + 2] + bf_lo(rcv[2 * j + 1]), bf_lo(xp[2 * j + 1])), fmaf(gb.y, acc[4 * j + 3] + bf_hi(rcv[2 * j + 1]), bf_hi(xp[2 * j + 1])));
                }
            }
#pragma unroll
            for (int j = 0; j < 8; j += 2) {
                const int cg = j + sm_cg;
                stsm4(abase + sm_off + ((cg ^ sm_sw) << 4), oo[2 * j], oo[2 * j + 1], oo[2 * j + 2], oo[2 * j + 3]);
            }
            staged();
        }
        named_bar(1, 256);
        if (ct == 0) {
            unsigned old = atomicInc(&g_done, NCTA + NAUX - 1);
            if (old == NCTA + NAUX - 1) g_epoch = tag;
        }
        cluster_arrive();
        cluster_wait();
    }
}

typedef CUresult (*EncodeFn)(CUtensorMap*, CUtensorMapDataType, cuuint32_t, void*, const cuuint64_t*, const cuuint64_t*, const cuuint32_t*,
                             const cuuint32_t*, CUtensorMapInterleave, CUtensorMapSwizzle, CUtensorMapL2promotion, CUtensorMapFloatOOBfill);

void make_map(EncodeFn enc, CUtensorMap* m, const void* ptr, uint64_t rows, uint64_t cols, uint32_t box_rows, uint32_t box_cols, bool swz) {
    cuuint64_t dims[2] = {cols, rows};
    cuuint64_t strides[1] = {cols * 2};
    cuuint32_t box[2] = {box_cols, box_rows};
    cuuint32_t es[2] = {1, 1};
    enc(m, CU_TENSOR_MAP_DATA_TYPE_BFLOAT16, 2, const_cast<void*>(ptr), dims, strides, box, es, CU_TENSOR_MAP_INTERLEAVE_NONE,
        swz ? CU_TENSOR_MAP_SWIZZLE_128B : CU_TENSOR_MAP_SWIZZLE_NONE, CU_TENSOR_MAP_L2_PROMOTION_L2_128B, CU_TENSOR_MAP_FLOAT_OOB_FILL_NONE);
}

}

extern "C" void kernel_launch(void* const* d_in, const int* in_sizes, int n_in, void* d_out, int out_size) {
    static EncodeFn enc = nullptr;
    static void *pxn, *ppq, *pz;
    if (!enc) {
        void* fn = nullptr;
        cudaDriverEntryPointQueryResult q;
        cudaGetDriverEntryPoint("cuTensorMapEncodeTiled", &fn, cudaEnableDefault, &q);
        enc = (EncodeFn)fn;
        cudaGetSymbolAddress(&pxn, g_xn);
        cudaGetSymbolAddress(&ppq, g_pq);
        cudaGetSymbolAddress(&pz, g_z);
        cudaFuncSetAttribute(mega_kernel, cudaFuncAttributeMaxDynamicSharedMemorySize, SMEM_BYTES);
    }
    Params p = {};
    p.x = (const __nv_bfloat16*)d_in[0];
    p.wre = (const __nv_bfloat16*)d_in[1];
    p.wim = (const __nv_bfloat16*)d_in[2];
    p.dr = (const __nv_bfloat16*)d_in[3];
    p.di = (const __nv_bfloat16*)d_in[4];
    p.wg = (const __nv_bfloat16*)d_in[6];
    p.wu = (const __nv_bfloat16*)d_in[7];
    p.wd = (const __nv_bfloat16*)d_in[8];
    p.c = (const __nv_bfloat16*)d_in[9];
    p.wmod = (const __nv_bfloat16*)d_in[10];
    make_map(enc, &p.m[M_WRE], d_in[1], S_, S_, 64, 64, true);
    make_map(enc, &p.m[M_WIM], d_in[2], S_, S_, 64, 64, true);
    make_map(enc, &p.m[M_XN], pxn, S_, D_, 64, 64, true);
    make_map(enc, &p.m[M_PQ], ppq, S_, 2 * D_, 64, 64, true);
    make_map(enc, &p.m[M_DR], d_in[3], D_, D_, 64, 64, true);
    make_map(enc, &p.m[M_DI], d_in[4], D_, D_, 64, 64, true);
    make_map(enc, &p.m[M_Z], pz, S_, D_, 64, 64, true);
    make_map(enc, &p.m[M_WG], d_in[6], D_, F_, 64, 64, true);
    make_map(enc, &p.m[M_WU], d_in[7], D_, F_, 64, 64, true);
    make_map(enc, &p.m[M_WD], d_in[8], F_, D_, 64, 64, true);
    make_map(enc, &p.m[M_OUT], d_out, S_, D_, 64, 64, true);
    make_map(enc, &p.m[M_WMODS], d_in[10], D_, 6 * D_, 64, 64, true);

    cudaLaunchConfig_t cfg = {};
    cfg.gridDim = dim3(NCTA + NAUX);
    cfg.blockDim = dim3(384);
    cfg.dynamicSmemBytes = SMEM_BYTES;
    cfg.stream = cudaStreamPerThread;
    cudaLaunchAttribute at[1];
    at[0].id = cudaLaunchAttributeClusterDimension;
    at[0].val.clusterDim.x = 2; at[0].val.clusterDim.y = 1; at[0].val.clusterDim.z = 1;
    cfg.attrs = at; cfg.numAttrs = 1;
    cudaLaunchKernelEx(&cfg, mega_kernel, p);
}
```

```cpp
#include <cuda_runtime.h>
#include <cuda_bf16.h>
#include <cuda.h>
#include <stdint.h>

namespace {

constexpr int S_ = 2048, D_ = 512, F_ = 1376;
constexpr int NCTA = 128;
constexpr int NAUX = 4;
constexpr int NB = 9;
constexpr int NA = 4;
constexpr int NA1 = 6;
constexpr int NB1 = 7;
constexpr uint32_t OFF_B = 0;
constexpr uint32_t OFF_A = NB * 16384;
constexpr uint32_t OFF_AUX = OFF_A + 2 * NA * 8192;
constexpr uint32_t OFF_ONES = OFF_AUX;
constexpr uint32_t OFF_CA1 = OFF_ONES + 1024;
constexpr uint32_t OFF_SA = OFF_CA1 + 128 * 4;
constexpr uint32_t OFF_GA = OFF_SA + 128 * 16;
constexpr uint32_t OFF_CB1 = OFF_GA + 64 * 4;
constexpr uint32_t OFF_GB = OFF_CB1 + 64 * 4;
constexpr uint32_t OFF_BX = OFF_GB + 64 * 4;
constexpr uint32_t OFF_AX = OFF_BX + 2 * 176 * 16;
constexpr uint32_t OFF_ZERO = OFF_AX + 2048;
constexpr uint32_t OFF_ST = OFF_ZERO + 1024;
constexpr uint32_t OFF_RSP = OFF_ST + 1024;
constexpr uint32_t OFF_BAR = OFF_RSP + 512;
constexpr uint32_t BAR_FULLB = OFF_BAR;
constexpr uint32_t BAR_EMPTYB = BAR_FULLB + 8 * NB;
constexpr uint32_t BAR_FULLA = BAR_EMPTYB + 8 * NB;
constexpr uint32_t BAR_EMPTYA = BAR_FULLA + 16 * NA1;
constexpr uint32_t BAR_PEMPTYA = BAR_EMPTYA + 16 * NA1;
constexpr uint32_t BAR_PRDY = BAR_PEMPTYA + 16 * NA1;
constexpr uint32_t BAR_RFULL = BAR_PRDY + 16;
constexpr uint32_t BAR_AUX = BAR_RFULL + 16;
constexpr uint32_t BAR_DEP = BAR_AUX + 24;
constexpr uint32_t BAR_STG = BAR_DEP + 16;
constexpr uint32_t BAR_XARR = BAR_STG + 128;
constexpr uint32_t SMEM_USED = BAR_XARR + 8;
constexpr uint32_t SMEM_BYTES = SMEM_USED;
static_assert(SMEM_BYTES <= 232448, "smem");
constexpr uint32_t P2_SLOTS = 4u | (5u << 4) | (6u << 8) | (0u << 12) | (7u << 16) | (8u << 20) | (1u << 24) | (2u << 28);

enum { M_WRE = 0, M_WIM, M_XN, M_PQ, M_DR, M_DI, M_Z, M_WG, M_WU, M_WD, M_OUT, M_WMODS, M_COUNT };

struct alignas(64) Params {
    const __nv_bfloat16* x;
    const __nv_bfloat16* c;
    const __nv_bfloat16* wmod;
    const __nv_bfloat16* wg;
    const __nv_bfloat16* wu;
    const __nv_bfloat16* dr;
    const __nv_bfloat16* di;
    const __nv_bfloat16* wd;
    const __nv_bfloat16* wre;
    const __nv_bfloat16* wim;
    const void* pad[6];
    CUtensorMap m[M_COUNT];
};

constexpr int CN_X = 0;
constexpr int CN_MOD = 8;
constexpr int CN_V = 10;
constexpr int CN_CS = 12;
constexpr int CN_1 = 16;
constexpr int CN_2 = CN_1 + 64;
constexpr int CN_3 = CN_2 + 32;
constexpr int CN_2S = CN_3 + 64;
constexpr int CN_COUNT = CN_2S + 32;

}

__device__ __align__(1024) __nv_bfloat16 g_xn[S_ * D_];
__device__ __align__(1024) __nv_bfloat16 g_pq[S_ * 2 * D_];
__device__ __align__(1024) __nv_bfloat16 g_z[S_ * D_];
__device__ __align__(1024) uint8_t g_h[32 * 8 * 3 * 8192];
__device__ __align__(1024) uint4 g_x2s[NCTA * 2 * 4 * 128];
__device__ __align__(1024) float2 g_stats[S_ * 8];
__device__ __align__(1024) float g_mod[6 * D_];
__device__ __align__(1024) float g_cs[4 * F_];
__device__ __align__(1024) float g_v[2 * D_];
__device__ __align__(1024) float g_rs[32 * 4 * 128];
__device__ __align__(1024) unsigned g_cnt[CN_COUNT * 32];
__device__ unsigned g_epoch;
__device__ unsigned g_done;
#define TRACE_INIT() do {} while (0)
#define TRACE(slot) do {} while (0)
#define TRACE2(ev, idx) do {} while (0)
#define TRACE_GT(slot) do {} while (0)

namespace {

__device__ __forceinline__ uint32_t smem_u32(const void* p) { return (uint32_t)__cvta_generic_to_shared(p); }
__device__ __forceinline__ void mbar_init(uint32_t bar, uint32_t cnt) { asm volatile("mbarrier.init.shared::cta.b64 [%0], %1;" :: "r"(bar), "r"(cnt) : "memory"); }
__device__ __forceinline__ void mbar_expect_tx(uint32_t bar, uint32_t bytes) { asm volatile("mbarrier.arrive.expect_tx.shared::cta.b64 _, [%0], %1;" :: "r"(bar), "r"(bytes) : "memory"); }
__device__ __forceinline__ void mbar_arrive(uint32_t bar) { asm volatile("mbarrier.arrive.shared::cta.b64 _, [%0];" :: "r"(bar) : "memory"); }
__device__ __forceinline__ uint32_t mapa(uint32_t addr, uint32_t cta) { uint32_t r; asm volatile("mapa.shared::cluster.u32 %0, %1, %2;" : "=r"(r) : "r"(addr), "r"(cta)); return r; }
__device__ __forceinline__ void mbar_arrive_cl(uint32_t cl_addr) { asm volatile("mbarrier.arrive.shared::cluster.b64 _, [%0];" :: "r"(cl_addr) : "memory"); }
__device__ __forceinline__ void mbar_wait(uint32_t bar, uint32_t parity) {
    asm volatile("{\n.reg .pred p;\n.reg .u32 c;\nmov.u32 c, 0;\n"
                 "MW_LOOP:\nmbarrier.try_wait.parity.shared::cta.b64 p, [%0], %1;\n@p bra MW_DONE;\n"
                 "add.u32 c, c, 1;\nsetp.lt.u32 p, c, 3000000;\n@p bra MW_LOOP;\ntrap;\nMW_DONE:\n}" :: "r"(bar), "r"(parity) : "memory");
}
__device__ __forceinline__ void mbar_wait_cl(uint32_t bar, uint32_t parity) {
    asm volatile("{\n.reg .pred p;\n.reg .u32 c;\nmov.u32 c, 0;\n"
                 "MW_LOOP:\nmbarrier.try_wait.parity.acquire.cluster.shared::cta.b64 p, [%0], %1;\n@p bra MW_DONE;\n"
                 "add.u32 c, c, 1;\nsetp.lt.u32 p, c, 3000000;\n@p bra MW_LOOP;\ntrap;\nMW_DONE:\n}" :: "r"(bar), "r"(parity) : "memory");
}
__device__ __forceinline__ void tma_load(uint32_t dst, const CUtensorMap* map, int c0, int c1, uint32_t bar) {
    asm volatile("cp.async.bulk.tensor.2d.shared::cluster.global.mbarrier::complete_tx::bytes [%0], [%1, {%3, %4}], [%2];"
                 :: "r"(dst), "l"(map), "r"(bar), "r"(c0), "r"(c1) : "memory");
}
__device__ __forceinline__ void tma_load_mc(uint32_t dst, const CUtensorMap* map, int c0, int c1, uint32_t bar) {
    asm volatile("cp.async.bulk.tensor.2d.shared::cluster.global.mbarrier::complete_tx::bytes.multicast::cluster [%0], [%1, {%3, %4}], [%2], %5;"
                 :: "r"(dst), "l"(map), "r"(bar), "r"(c0), "r"(c1), "h"((uint16_t)3) : "memory");
}
__device__ __forceinline__ void prefetch_tmap(const CUtensorMap* m) { asm volatile("prefetch.tensormap [%0];" :: "l"(m) : "memory"); }
__device__ __forceinline__ void bulk_prefetch(const void* p, uint32_t bytes) {
    asm volatile("cp.async.bulk.prefetch.L2.global [%0], %1;" :: "l"(p), "r"(bytes) : "memory");
}
__device__ __forceinline__ void tma_store(const CUtensorMap* map, uint32_t src, int c0, int c1) {
    asm volatile("cp.async.bulk.tensor.2d.global.shared::cta.bulk_group [%0, {%2, %3}], [%1];" :: "l"(map), "r"(src), "r"(c0), "r"(c1) : "memory");
}
__device__ __forceinline__ void bulk_commit() { asm volatile("cp.async.bulk.commit_group;" ::: "memory"); }
__device__ __forceinline__ void bulk_wait_all() { asm volatile("cp.async.bulk.wait_group 0;" ::: "memory"); }
__device__ __forceinline__ void fence_async_smem() { asm volatile("fence.proxy.async.shared::cta;" ::: "memory"); }
__device__ __forceinline__ void fence_async_global() { asm volatile("fence.proxy.async.global;" ::: "memory"); }
__device__ __forceinline__ bool elect_one() {
    uint32_t pred;
    asm volatile("{\n.reg .pred p;\nelect.sync _|p, 0xffffffff;\nselp.u32 %0, 1, 0, p;\n}" : "=r"(pred));
    return pred != 0;
}
__device__ __forceinline__ void cluster_arrive() { asm volatile("barrier.cluster.arrive.relaxed.aligned;" ::: "memory"); }
__device__ __forceinline__ void cluster_wait() { asm volatile("barrier.cluster.wait.aligned;" ::: "memory"); }
__device__ __forceinline__ void named_bar(int id, int n) { asm volatile("bar.sync %0, %1;" :: "r"(id), "r"(n) : "memory"); }
__device__ __forceinline__ void wgmma_fence() { asm volatile("wgmma.fence.sync.aligned;" ::: "memory"); }
__device__ __forceinline__ void wgmma_commit() { asm volatile("wgmma.commit_group.sync.aligned;" ::: "memory"); }
template <int N> __device__ __forceinline__ void wgmma_wait() { asm volatile("wgmma.wait_group.sync.aligned %0;" :: "n"(N) : "memory"); }
template <int R> __device__ __forceinline__ void reg_alloc() { asm volatile("setmaxnreg.inc.sync.aligned.u32 %0;" :: "n"(R)); }
template <int R> __device__ __forceinline__ void reg_dealloc() { asm volatile("setmaxnreg.dec.sync.aligned.u32 %0;" :: "n"(R)); }
__device__ __forceinline__ unsigned ld_relaxed(const unsigned* p) { unsigned v; asm volatile("ld.relaxed.gpu.global.u32 %0, [%1];" : "=r"(v) : "l"(p) : "memory"); return v; }
__device__ __forceinline__ void bulk_load(uint32_t dst, const void* g, uint32_t bytes, uint32_t bar) {
    asm volatile("cp.async.bulk.shared::cluster.global.mbarrier::complete_tx::bytes [%0], [%1], %2, [%3];" :: "r"(dst), "l"(g), "r"(bytes), "r"(bar) : "memory");
}
__device__ __forceinline__ void bulk_store(void* g, uint32_t src, uint32_t bytes) {
    asm volatile("cp.async.bulk.global.shared::cta.bulk_group [%0], [%1], %2;" :: "l"(g), "r"(src), "r"(bytes) : "memory");
}
__device__ __forceinline__ void sts_u4(uint32_t a, uint4 v) { asm volatile("st.shared.v4.u32 [%0], {%1, %2, %3, %4};" :: "r"(a), "r"(v.x), "r"(v.y), "r"(v.z), "r"(v.w) : "memory"); }
__device__ __forceinline__ void sts_f2(uint32_t a, float x, float y) { asm volatile("st.shared.v2.f32 [%0], {%1, %2};" :: "r"(a), "f"(x), "f"(y) : "memory"); }
__device__ __forceinline__ uint4 ldg_stream(const void* p) {
    uint4 v; asm volatile("ld.global.nc.L1::no_allocate.v4.u32 {%0, %1, %2, %3}, [%4];" : "=r"(v.x), "=r"(v.y), "=r"(v.z), "=r"(v.w) : "l"(p)); return v;
}
__device__ __forceinline__ uint64_t make_desc(uint32_t addr, uint32_t lbo, uint32_t sbo) {
    return (uint64_t)((addr & 0x3FFFF) >> 4) | ((uint64_t)(lbo >> 4) << 16) | ((uint64_t)(sbo >> 4) << 32) | ((uint64_t)1 << 62);
}
__device__ __forceinline__ uint64_t make_desc_ns(uint32_t addr, uint32_t lbo, uint32_t sbo) {
    return (uint64_t)((addr & 0x3FFFF) >> 4) | ((uint64_t)((lbo & 0x3FFFF) >> 4) << 16) | ((uint64_t)(sbo >> 4) << 32);
}
__device__ __forceinline__ uint32_t pack_bf16(float lo, float hi) {
    uint32_t r; asm("cvt.rn.bf16x2.f32 %0, %1, %2;" : "=r"(r) : "f"(hi), "f"(lo)); return r;
}
__device__ __forceinline__ float bf_lo(uint32_t v) { return __uint_as_float(v << 16); }
__device__ __forceinline__ float bf_hi(uint32_t v) { return __uint_as_float(v & 0xffff0000u); }
__device__ __forceinline__ void split_bf16(float v, uint32_t& hi, uint32_t& lo) {
    const __nv_bfloat16 h = __float2bfloat16_rn(v);
    hi = __bfloat16_as_ushort(h);
    lo = __bfloat16_as_ushort(__float2bfloat16_rn(v - __bfloat162float(h)));
}
__device__ __forceinline__ float bf_round(float v) { return __bfloat162float(__float2bfloat16_rn(v)); }
__device__ __forceinline__ void stsm4(uint32_t addr, uint32_t r0, uint32_t r1, uint32_t r2, uint32_t r3) {
    asm volatile("stmatrix.sync.aligned.m8n8.x4.shared.b16 [%0], {%1, %2, %3, %4};" :: "r"(addr), "r"(r0), "r"(r1), "r"(r2), "r"(r3));
}
__device__ __forceinline__ uint4 lds_u4(uint32_t a) { uint4 v; asm volatile("ld.shared.v4.u32 {%0, %1, %2, %3}, [%4];" : "=r"(v.x), "=r"(v.y), "=r"(v.z), "=r"(v.w) : "r"(a)); return v; }
__device__ __forceinline__ void sts_f(uint32_t a, float v) { asm volatile("st.shared.f32 [%0], %1;" :: "r"(a), "f"(v) : "memory"); }
__device__ __forceinline__ void st_async4u(uint32_t cl_addr, uint32_t a, uint32_t b, uint32_t c, uint32_t d, uint32_t cl_bar) {
    asm volatile("st.async.weak.shared::cluster.mbarrier::complete_tx::bytes.v4.b32 [%0], {%1, %2, %3, %4}, [%5];"
                 :: "r"(cl_addr), "r"(a), "r"(b), "r"(c), "r"(d), "r"(cl_bar) : "memory");
}
__device__ __forceinline__ float tanh_fast(float x) { float y; asm("tanh.approx.f32 %0, %1;" : "=f"(y) : "f"(x)); return y; }
template <int N> __device__ __forceinline__ void fence_regs(float (&a)[N]) {
#pragma unroll
    for (int i = 0; i < N; i++) asm volatile("" : "+f"(a[i]) :: "memory");
}
__device__ __forceinline__ void cnt_add(int idx) { asm volatile("red.relaxed.gpu.global.add.u32 [%0], 1;" :: "l"(g_cnt + idx * 32) : "memory"); }
template <int SLEEP_NS>
__device__ __forceinline__ void cnt_wait(int idx, unsigned tag, unsigned per) {
    const unsigned target = tag * per;
    const unsigned* c = g_cnt + idx * 32;
    unsigned it = 0;
    while ((int)(ld_relaxed(c) - target) < 0) {
        if (SLEEP_NS > 0) __nanosleep(SLEEP_NS);
        if (++it > 4000000u) __trap();
    }
    asm volatile("fence.acquire.gpu;" ::: "memory");
}

template <int TB>
__device__ __forceinline__ void wgmma_n128(float (&d)[64], uint64_t da, uint64_t db, int scale_d) {
    asm volatile("{\n.reg .pred p;\nsetp.ne.b32 p, %66, 0;\n"
        "wgmma.mma_async.sync.aligned.m64n128k16.f32.bf16.bf16 {"
        "%0, %1, %2, %3, %4, %5, %6, %7, %8, %9, %10, %11, %12, %13, %14, %15, "
        "%16, %17, %18, %19, %20, %21, %22, %23, %24, %25, %26, %27, %28, %29, %30, %31, "
        "%32, %33, %34, %35, %36, %37, %38, %39, %40, %41, %42, %43, %44, %45, %46, %47, "
        "%48, %49, %50, %51, %52, %53, %54, %55, %56, %57, %58, %59, %60, %61, %62, %63}, "
        "%64, %65, p, 1, 1, 0, %67;\n}"
        : "+f"(d[0]), "+f"(d[1]), "+f"(d[2]), "+f"(d[3]), "+f"(d[4]), "+f"(d[5]), "+f"(d[6]), "+f"(d[7]),
          "+f"(d[8]), "+f"(d[9]), "+f"(d[10]), "+f"(d[11]), "+f"(d[12]), "+f"(d[13]), "+f"(d[14]), "+f"(d[15]),
          "+f"(d[16]), "+f"(d[17]), "+f"(d[18]), "+f"(d[19]), "+f"(d[20]), "+f"(d[21]), "+f"(d[22]), "+f"(d[23]),
          "+f"(d[24]), "+f"(d[25]), "+f"(d[26]), "+f"(d[27]), "+f"(d[28]), "+f"(d[29]), "+f"(d[30]), "+f"(d[31]),
          "+f"(d[32]), "+f"(d[33]), "+f"(d[34]), "+f"(d[35]), "+f"(d[36]), "+f"(d[37]), "+f"(d[38]), "+f"(d[39]),
          "+f"(d[40]), "+f"(d[41]), "+f"(d[42]), "+f"(d[43]), "+f"(d[44]), "+f"(d[45]), "+f"(d[46]), "+f"(d[47]),
          "+f"(d[48]), "+f"(d[49]), "+f"(d[50]), "+f"(d[51]), "+f"(d[52]), "+f"(d[53]), "+f"(d[54]), "+f"(d[55]),
          "+f"(d[56]), "+f"(d[57]), "+f"(d[58]), "+f"(d[59]), "+f"(d[60]), "+f"(d[61]), "+f"(d[62]), "+f"(d[63])
        : "l"(da), "l"(db), "r"(scale_d), "n"(TB));
}
template <int TB>
__device__ __forceinline__ void wgmma_n176(float (&d)[88], uint64_t da, uint64_t db, int scale_d) {
    asm volatile("{\n.reg .pred p;\nsetp.ne.b32 p, %90, 0;\n"
        "wgmma.mma_async.sync.aligned.m64n176k16.f32.bf16.bf16 {"
        "%0, %1, %2, %3, %4, %5, %6, %7, %8, %9, %10, %11, %12, %13, %14, %15, "
        "%16, %17, %18, %19, %20, %21, %22, %23, %24, %25, %26, %27, %28, %29, %30, %31, "
        "%32, %33, %34, %35, %36, %37, %38, %39, %40, %41, %42, %43, %44, %45, %46, %47, "
        "%48, %49, %50, %51, %52, %53, %54, %55, %56, %57, %58, %59, %60, %61, %62, %63, "
        "%64, %65, %66, %67, %68, %69, %70, %71, %72, %73, %74, %75, %76, %77, %78, %79, "
        "%80, %81, %82, %83, %84, %85, %86, %87}, "
        "%88, %89, p, 1, 1, 0, %91;\n}"
        : "+f"(d[0]), "+f"(d[1]), "+f"(d[2]), "+f"(d[3]), "+f"(d[4]), "+f"(d[5]), "+f"(d[6]), "+f"(d[7]),
          "+f"(d[8]), "+f"(d[9]), "+f"(d[10]), "+f"(d[11]), "+f"(d[12]), "+f"(d[13]), "+f"(d[14]), "+f"(d[15]),
          "+f"(d[16]), "+f"(d[17]), "+f"(d[18]), "+f"(d[19]), "+f"(d[20]), "+f"(d[21]), "+f"(d[22]), "+f"(d[23]),
          "+f"(d[24]), "+f"(d[25]), "+f"(d[26]), "+f"(d[27]), "+f"(d[28]), "+f"(d[29]), "+f"(d[30]), "+f"(d[31]),
          "+f"(d[32]), "+f"(d[33]), "+f"(d[34]), "+f"(d[35]), "+f"(d[36]), "+f"(d[37]), "+f"(d[38]), "+f"(d[39]),
          "+f"(d[40]), "+f"(d[41]), "+f"(d[42]), "+f"(d[43]), "+f"(d[44]), "+f"(d[45]), "+f"(d[46]), "+f"(d[47]),
          "+f"(d[48]), "+f"(d[49]), "+f"(d[50]), "+f"(d[51]), "+f"(d[52]), "+f"(d[53]), "+f"(d[54]), "+f"(d[55]),
          "+f"(d[56]), "+f"(d[57]), "+f"(d[58]), "+f"(d[59]), "+f"(d[60]), "+f"(d[61]), "+f"(d[62]), "+f"(d[63]),
          "+f"(d[64]), "+f"(d[65]), "+f"(d[66]), "+f"(d[67]), "+f"(d[68]), "+f"(d[69]), "+f"(d[70]), "+f"(d[71]),
          "+f"(d[72]), "+f"(d[73]), "+f"(d[74]), "+f"(d[75]), "+f"(d[76]), "+f"(d[77]), "+f"(d[78]), "+f"(d[79]),
          "+f"(d[80]), "+f"(d[81]), "+f"(d[82]), "+f"(d[83]), "+f"(d[84]), "+f"(d[85]), "+f"(d[86]), "+f"(d[87])
        : "l"(da), "l"(db), "r"(scale_d), "n"(TB));
}
template <int TB>
__device__ __forceinline__ void wgmma_n8(float (&d)[4], uint64_t da, uint64_t db, int scale_d) {
    asm volatile("{\n.reg .pred p;\nsetp.ne.b32 p, %6, 0;\n"
        "wgmma.mma_async.sync.aligned.m64n8k16.f32.bf16.bf16 {"
        "%0, %1, %2, %3}, "
        "%4, %5, p, 1, 1, 0, %7;\n}"
        : "+f"(d[0]), "+f"(d[1]), "+f"(d[2]), "+f"(d[3])
        : "l"(da), "l"(db), "r"(scale_d), "n"(TB));
}
template <int TB>
__device__ __forceinline__ void wgmma_n256(float (&d)[128], uint64_t da, uint64_t db, int scale_d) {
    asm volatile("{\n.reg .pred p;\nsetp.ne.b32 p, %130, 0;\n"
        "wgmma.mma_async.sync.aligned.m64n256k16.f32.bf16.bf16 {"
        "%0, %1, %2, %3, %4, %5, %6, %7, %8, %9, %10, %11, %12, %13, %14, %15, "
        "%16, %17, %18, %19, %20, %21, %22, %23, %24, %25, %26, %27, %28, %29, %30, %31, "
        "%32, %33, %34, %35, %36, %37, %38, %39, %40, %41, %42, %43, %44, %45, %46, %47, "
        "%48, %49, %50, %51, %52, %53, %54, %55, %56, %57, %58, %59, %60, %61, %62, %63, "
        "%64, %65, %66, %67, %68, %69, %70, %71, %72, %73, %74, %75, %76, %77, %78, %79, "
        "%80, %81, %82, %83, %84, %85, %86, %87, %88, %89, %90, %91, %92, %93, %94, %95, "
        "%96, %97, %98, %99, %100, %101, %102, %103, %104, %105, %106, %107, %108, %109, %110, %111, "
        "%112, %113, %114, %115, %116, %117, %118, %119, %120, %121, %122, %123, %124, %125, %126, %127}, "
        "%128, %129, p, 1, 1, 0, %131;\n}"
        : "+f"(d[0]), "+f"(d[1]), "+f"(d[2]), "+f"(d[3]), "+f"(d[4]), "+f"(d[5]), "+f"(d[6]), "+f"(d[7]),
          "+f"(d[8]), "+f"(d[9]), "+f"(d[10]), "+f"(d[11]), "+f"(d[12]), "+f"(d[13]), "+f"(d[14]), "+f"(d[15]),
          "+f"(d[16]), "+f"(d[17]), "+f"(d[18]), "+f"(d[19]), "+f"(d[20]), "+f"(d[21]), "+f"(d[22]), "+f"(d[23]),
          "+f"(d[24]), "+f"(d[25]), "+f"(d[26]), "+f"(d[27]), "+f"(d[28]), "+f"(d[29]), "+f"(d[30]), "+f"(d[31]),
          "+f"(d[32]), "+f"(d[33]), "+f"(d[34]), "+f"(d[35]), "+f"(d[36]), "+f"(d[37]), "+f"(d[38]), "+f"(d[39]),
          "+f"(d[40]), "+f"(d[41]), "+f"(d[42]), "+f"(d[43]), "+f"(d[44]), "+f"(d[45]), "+f"(d[46]), "+f"(d[47]),
          "+f"(d[48]), "+f"(d[49]), "+f"(d[50]), "+f"(d[51]), "+f"(d[52]), "+f"(d[53]), "+f"(d[54]), "+f"(d[55]),
          "+f"(d[56]), "+f"(d[57]), "+f"(d[58]), "+f"(d[59]), "+f"(d[60]), "+f"(d[61]), "+f"(d[62]), "+f"(d[63]),
          "+f"(d[64]), "+f"(d[65]), "+f"(d[66]), "+f"(d[67]), "+f"(d[68]), "+f"(d[69]), "+f"(d[70]), "+f"(d[71]),
          "+f"(d[72]), "+f"(d[73]), "+f"(d[74]), "+f"(d[75]), "+f"(d[76]), "+f"(d[77]), "+f"(d[78]), "+f"(d[79]),
          "+f"(d[80]), "+f"(d[81]), "+f"(d[82]), "+f"(d[83]), "+f"(d[84]), "+f"(d[85]), "+f"(d[86]), "+f"(d[87]),
          "+f"(d[88]), "+f"(d[89]), "+f"(d[90]), "+f"(d[91]), "+f"(d[92]), "+f"(d[93]), "+f"(d[94]), "+f"(d[95]),
          "+f"(d[96]), "+f"(d[97]), "+f"(d[98]), "+f"(d[99]), "+f"(d[100]), "+f"(d[101]), "+f"(d[102]), "+f"(d[103]),
          "+f"(d[104]), "+f"(d[105]), "+f"(d[106]), "+f"(d[107]), "+f"(d[108]), "+f"(d[109]), "+f"(d[110]), "+f"(d[111]),
          "+f"(d[112]), "+f"(d[113]), "+f"(d[114]), "+f"(d[115]), "+f"(d[116]), "+f"(d[117]), "+f"(d[118]), "+f"(d[119]),
          "+f"(d[120]), "+f"(d[121]), "+f"(d[122]), "+f"(d[123]), "+f"(d[124]), "+f"(d[125]), "+f"(d[126]), "+f"(d[127])
        : "l"(da), "l"(db), "r"(scale_d), "n"(TB));
}

template <bool B> struct BoolC { static constexpr bool value = B; };
template <int I> struct IntC { static constexpr int value = I; };
__device__ __forceinline__ uint32_t bit(uint32_t mask, int i) { return (mask >> i) & 1u; }
__device__ __forceinline__ uint32_t a_slot_addr(uint32_t sb, int w, int slot) {
    return slot < NA ? sb + OFF_A + w * (NA * 8192) + slot * 8192 : sb + OFF_B + (7 + w) * 16384 + (slot - NA) * 8192;
}

constexpr int AX_NS = 5;
constexpr uint32_t AX_A = AX_NS * 32768;
constexpr uint32_t AX_OUT = AX_A + 3 * 8192;
constexpr uint32_t AX_BAR = AX_OUT + 6144;
__device__ __forceinline__ void aux_put_a(uint8_t* smem, int which, int row, int d, float v) {
    const int kb = d >> 6, c = d & 63;
    *(__nv_bfloat16*)(smem + AX_A + which * 8192 + kb * 1024 + row * 128 + (((c >> 3) ^ row) << 4) + (c & 7) * 2) = __float2bfloat16_rn(v);
}
__device__ __forceinline__ void aux_cta(const Params& p, uint8_t* smem, uint32_t sb, int a, unsigned tag, long long t_base_) {
    const int tid = threadIdx.x, lane = tid & 31;
    const int warp = __shfl_sync(0xffffffffu, tid >> 5, 0);
    if (tid == 0) {
        for (int s = 0; s < AX_NS; s++) { mbar_init(sb + AX_BAR + 8 * s, 1); mbar_init(sb + AX_BAR + 8 * (AX_NS + s), 1); }
        asm volatile("fence.mbarrier_init.release.cluster;" ::: "memory");
    }
    for (int i = tid; i < 3 * 8192 / 16; i += 384) *(uint4*)(smem + AX_A + i * 16) = make_uint4(0, 0, 0, 0);
    __syncthreads();
    if (warp == 0) {
        if (elect_one()) {
            const CUtensorMap* mw = &p.m[a < 2 ? M_WG : M_WU];
            const CUtensorMap* md = &p.m[a < 2 ? M_DR : M_DI];
            int slot = 0; uint32_t ph = 1;
#pragma unroll 1
            for (int st = 0; st < 48; st++) {
                const uint32_t full = sb + AX_BAR + 8 * slot, dst = sb + slot * 32768;
                mbar_wait(sb + AX_BAR + 8 * (AX_NS + slot), ph);
                mbar_expect_tx(full, 32768);
                const int kb = st & 7;
#pragma unroll
                for (int c = 0; c < 4; c++) {
                    if (st < 24) tma_load(dst + c * 8192, &p.m[M_WMODS], a * 768 + (st >> 3) * 256 + c * 64, kb * 64, full);
                    else if (st < 32) tma_load(dst + c * 8192, md, kb * 64, (a & 1) * 256 + c * 64, full);
                    else tma_load(dst + c * 8192, mw, (a & 1) * 688 + ((st - 32) >> 3) * 256 + c * 64, kb * 64, full);
                }
                if (++slot == AX_NS) { slot = 0; ph ^= 1; }
            }
        }
        return;
    }
    if (warp < 4) return;
    if (warp >= 8) {
        const int t = tid - 256, cg = t % 22, rq = t / 22;
        named_bar(2, 256);
        float* red = (float*)(smem + AX_OUT + 6144 + 256);
        if (rq < 4) {
            const __nv_bfloat16* W = (a < 2 ? p.wg : p.wu) + (size_t)(rq * 128) * F_ + (a & 1) * 688 + 512 + cg * 8;
            float cs[8], bi[8];
#pragma unroll
            for (int e = 0; e < 8; e++) { cs[e] = 0.f; bi[e] = 0.f; }
#pragma unroll 1
            for (int r0 = 0; r0 < 128; r0 += 16) {
                uint4 v[16]; float m1[16], m0[16];
#pragma unroll
                for (int k = 0; k < 16; k++) v[k] = ldg_stream(W + (size_t)(r0 + k) * F_);
#pragma unroll
                for (int k = 0; k < 4; k++) {
                    const float4 q1 = __ldcg((const float4*)(g_mod + 4 * 512 + rq * 128 + r0 + k * 4)), q0 = __ldcg((const float4*)(g_mod + 3 * 512 + rq * 128 + r0 + k * 4));
                    m1[4 * k] = q1.x; m1[4 * k + 1] = q1.y; m1[4 * k + 2] = q1.z; m1[4 * k + 3] = q1.w;
                    m0[4 * k] = q0.x; m0[4 * k + 1] = q0.y; m0[4 * k + 2] = q0.z; m0[4 * k + 3] = q0.w;
                }
#pragma unroll
                for (int k = 0; k < 16; k++) {
                    const float f[8] = {bf_lo(v[k].x), bf_hi(v[k].x), bf_lo(v[k].y), bf_hi(v[k].y), bf_lo(v[k].z), bf_hi(v[k].z), bf_lo(v[k].w), bf_hi(v[k].w)};
                    const float c1 = bf_round(1.f + m1[k]);
#pragma unroll
                    for (int e = 0; e < 8; e++) { cs[e] = fmaf(c1, f[e], cs[e]); bi[e] = fmaf(m0[k], f[e], bi[e]); }
                }
            }
#pragma unroll
            for (int e = 0; e < 8; e++) { red[(rq * 2 + 0) * 176 + cg * 8 + e] = cs[e]; red[(rq * 2 + 1) * 176 + cg * 8 + e] = bi[e]; }
        }
        named_bar(3, 128);
        float* outb = (float*)(smem + AX_OUT);
        for (int i = t; i < 352; i += 128) {
            const int row = i / 176, c = i % 176;
            outb[row * 768 + 512 + c] = (red[(0 + row) * 176 + c] + red[(2 + row) * 176 + c]) + (red[(4 + row) * 176 + c] + red[(6 + row) * 176 + c]);
        }
        fence_async_smem();
        named_bar(4, 256);
        return;
    }
    const int wt = tid - 128;
    for (int d = wt; d < 512; d += 128) {
        const float cval = __bfloat162float(p.c[d]);
        aux_put_a(smem, 0, 0, d, __fdividef(cval, 1.f + __expf(-cval)));
    }
    fence_async_smem();
    named_bar(1, 128);
    float* outb = (float*)(smem + AX_OUT);
    int slot = 0; uint32_t ph = 0;
    auto run_group = [&](auto kmaj, int which, int g0) {
        float acc[128];
#pragma unroll
        for (int i = 0; i < 128; i++) acc[i] = 0.f;
        fence_regs(acc);
        int pslot = 0;
#pragma unroll 1
        for (int kb = 0; kb < 8; kb++) {
            mbar_wait(sb + AX_BAR + 8 * slot, ph);
            const uint64_t da = make_desc(sb + AX_A + which * 8192 + kb * 1024, 16, 0);
            const uint64_t db = decltype(kmaj)::value ? make_desc(sb + slot * 32768, 16, 1024) : make_desc(sb + slot * 32768, 8192, 1024);
            wgmma_fence();
#pragma unroll
            for (int k = 0; k < 4; k++) {
                if (decltype(kmaj)::value) wgmma_n256<0>(acc, da + k * 2, db + k * 2, 1);
                else wgmma_n256<1>(acc, da + k * 2, db + k * 128, 1);
            }
            wgmma_commit();
            wgmma_wait<1>();
            if (kb > 0 && wt == 0) mbar_arrive(sb + AX_BAR + 8 * (AX_NS + pslot));
            pslot = slot;
            if (++slot == AX_NS) { slot = 0; ph ^= 1; }
        }
        wgmma_wait<0>();
        fence_regs(acc);
        if (wt == 0) mbar_arrive(sb + AX_BAR + 8 * (AX_NS + pslot));
        if (wt < 8) {
            const int row = wt >> 2, c0 = (wt & 3) * 2;
            if (row == 0 || which == 2) {
#pragma unroll
                for (int i = 0; i < 32; i++) {
                    const int c = g0 + i * 8 + c0;
                    const float v0 = which == 0 ? bf_round(acc[4 * i]) : acc[4 * i], v1 = which == 0 ? bf_round(acc[4 * i + 1]) : acc[4 * i + 1];
                    outb[row * 768 + c] = v0; outb[row * 768 + c + 1] = v1;
                }
            }
        }
    };
#pragma unroll 1
    for (int g = 0; g < 3; g++) run_group(BoolC<false>{}, 0, g * 256);
    {
        fence_async_smem();
        named_bar(1, 128);
        if (wt == 0) {
            bulk_store(g_mod + a * 768, sb + AX_OUT, 3072);
            bulk_commit(); bulk_wait_all();
            cnt_add(CN_MOD); cnt_add(CN_MOD + 1);
            TRACE(51);
            cnt_wait<0>(CN_MOD, tag, NAUX);
        }
        named_bar(1, 128);
        named_bar(2, 256);
        float t[3][4];
#pragma unroll
        for (int k = 0; k < 4; k++) { const int d = wt + 128 * k; t[0][k] = __ldcg(g_mod + d); t[1][k] = __ldcg(g_mod + 4 * 512 + d); t[2][k] = __ldcg(g_mod + 3 * 512 + d); }
#pragma unroll
        for (int k = 0; k < 4; k++) { const int d = wt + 128 * k; aux_put_a(smem, 1, 0, d, t[0][k]); aux_put_a(smem, 2, 0, d, 1.f + t[1][k]); aux_put_a(smem, 2, 1, d, t[2][k]); }
        fence_async_smem();
        named_bar(1, 128);
    }
    run_group(BoolC<true>{}, 1, 0);
    {
        fence_async_smem();
        named_bar(1, 128);
        if (wt == 0) {
            bulk_store(g_v + a * 256, sb + AX_OUT, 1024);
            bulk_commit(); bulk_wait_all();
            cnt_add(CN_V); cnt_add(CN_V + 1);
            TRACE(53);
        }
        named_bar(1, 128);
    }
#pragma unroll 1
    for (int g = 0; g < 2; g++) run_group(BoolC<false>{}, 2, g * 256);
    fence_async_smem();
    named_bar(4, 256);
    if (wt == 0) {
        const int isu = a >> 1, col0 = (a & 1) * 688;
        bulk_store(g_cs + (isu * 2 + 0) * F_ + col0, sb + AX_OUT, 688 * 4);
        bulk_store(g_cs + (isu * 2 + 1) * F_ + col0, sb + AX_OUT + 768 * 4, 688 * 4);
        bulk_commit(); bulk_wait_all();
        cnt_add(CN_CS); cnt_add(CN_CS + 1);
        TRACE(54);
        unsigned old = atomicInc(&g_done, NCTA + NAUX - 1);
        if (old == NCTA + NAUX - 1) g_epoch = tag;
    }
}

__global__ void __launch_bounds__(384, 1) mega_kernel(const __grid_constant__ Params p) {
    extern __shared__ __align__(1024) uint8_t smem_raw[];
    TRACE_INIT();
    const int tid = threadIdx.x;
    const int b = blockIdx.x;
    const int lane = tid & 31;
    uint4 xv[2][2];
    if (tid >= 128 && b < NCTA) {
        const __nv_bfloat16* xr = p.x + (size_t)(b * 16 + ((tid - 128) >> 5) * 2) * D_ + lane * 8;
#pragma unroll
        for (int rr = 0; rr < 2; rr++) { xv[rr][0] = ldg_stream(xr + rr * D_); xv[rr][1] = ldg_stream(xr + rr * D_ + 256); }
    }
    const unsigned tag = ld_relaxed(&g_epoch) + 1;
    const uint32_t sb = smem_u32(smem_raw);
    if (sb & 1023u) __trap();
    if (b >= NCTA) {
        aux_cta(p, smem_raw, sb, b - NCTA, tag, 0);
        return;
    }
    const int warp = __shfl_sync(0xffffffffu, tid >> 5, 0);
    const int rho = b & 1;
    const int rb = b >> 3;
    const int pi = (b >> 1) & 3;
    const int part1 = pi >> 1, nt1 = (pi & 1) * 2 + rho;
    const int j3 = pi * 2 + rho;
    auto slice3 = [&](int kk) { return (j3 + kk) & 7; };
    const int col2 = pi * 128 + rho * 64;

    if (tid == 0) TRACE_GT(0);
    {
        constexpr int NBAR = (SMEM_USED - OFF_BAR) / 8;
        if (elect_one()) {
#pragma unroll 1
            for (int i = warp; i < NBAR; i += 12) {
                uint32_t a = OFF_BAR + 8 * i;
                uint32_t cnt = 1;
                if (a >= BAR_EMPTYB && a < BAR_FULLA) cnt = 2;
                else if (a == BAR_XARR) cnt = 8;
                mbar_init(sb + a, cnt);
            }
            asm volatile("fence.mbarrier_init.release.cluster;" ::: "memory");
        }
    }
    if (warp == 2 && lane < M_COUNT) prefetch_tmap(&p.m[lane]);
    if (warp == 3) {
#pragma unroll
        for (int k = 0; k < 2; k++) asm volatile("st.shared.v4.u32 [%0], {%1, %1, %1, %1};" :: "r"(sb + OFF_ONES + (lane + 32 * k) * 16), "r"(0x3f803f80u) : "memory");
#pragma unroll
        for (int k = 0; k < 2; k++) asm volatile("st.shared.v4.u32 [%0], {%1, %1, %1, %1};" :: "r"(sb + OFF_ZERO + (lane + 32 * k) * 16), "r"(0u) : "memory");
        fence_async_smem();
    }
    const uint32_t peer_sb = mapa(sb, rho ^ 1);
    __syncthreads();
    cluster_arrive();

    if (warp < 4) {
        cluster_wait();
        if (tid == 0) TRACE(33);
        reg_dealloc<72>();
        if (warp == 0) {
            if (elect_one()) {
                cnt_wait<0>(CN_X + ((b >> 1) & 7), tag, 128);
                fence_async_global();
                uint32_t ph = 0x1ff;
                TRACE(1);
                int slot = 0;
#pragma unroll 1
                for (int kb = 0; kb < 32; kb++) {
                    uint32_t full = sb + BAR_FULLB + 8 * slot, dst = sb + OFF_B + slot * 16384;
                    mbar_wait(sb + BAR_EMPTYB + 8 * slot, bit(ph, slot));
                    TRACE2(6, kb);
                    mbar_expect_tx(full, 16384);
                    tma_load(dst, &p.m[M_XN], nt1 * 128, kb * 64, full);
                    tma_load(dst + 8192, &p.m[M_XN], nt1 * 128 + 64, kb * 64, full);
                    if (kb == 4) { bulk_prefetch((const char*)p.dr + (size_t)b * 4096, 4096); bulk_prefetch((const char*)p.di + (size_t)b * 4096, 4096); }
                    if (kb == 10) bulk_prefetch((const char*)p.wg + (size_t)b * 11008, 11008);
                    if (kb == 16) bulk_prefetch((const char*)p.wu + (size_t)b * 11008, 11008);
                    if (kb == 26) bulk_prefetch((const char*)p.wd + (size_t)b * 11008, 11008);
                    ph ^= 1u << slot;
                    if (++slot == NB1) slot = 0;
                }
#pragma unroll 1
                for (int kk = 0; kk < 8; kk++) {
                    slot = (P2_SLOTS >> (4 * kk)) & 15;
                    uint32_t full = sb + BAR_FULLB + 8 * slot, dst = sb + OFF_B + slot * 16384;
                    if (slot >= 7) {
                        mbar_wait(sb + BAR_EMPTYA + 8 * (NA1 * (slot - 7) + 4), 0);
                        mbar_wait(sb + BAR_EMPTYA + 8 * (NA1 * (slot - 7) + 5), 0);
                    } else {
                        mbar_wait(sb + BAR_EMPTYB + 8 * slot, bit(ph, slot));
                    }
                    mbar_expect_tx(full, 16384);
                    const int c = (pi + (kk >> 1)) & 3, kcol = ((c & 1) * 2 + rho) * 128 + (kk & 1) * 64;
                    const CUtensorMap* md = &p.m[(c >> 1) ? M_DI : M_DR];
                    tma_load(dst, md, kcol, col2, full);
                    tma_load(dst + 8192, md, kcol, col2 ^ 64, full);
                    ph ^= 1u << slot;
                }
                slot = 3;
#pragma unroll 1
                for (int kk = 0; kk < 8; kk++) {
                    uint32_t dst = sb + OFF_B + slot * 16384;
                    uint32_t full = sb + BAR_FULLB + 8 * slot;
                    mbar_wait(sb + BAR_EMPTYB + 8 * slot, bit(ph, slot));
                    if (kk < 3) { mbar_wait(sb + BAR_EMPTYB + 8 * (slot + 1), bit(ph, slot + 1)); mbar_wait(sb + BAR_EMPTYB + 8 * (slot + 2), bit(ph, slot + 2)); }
                    mbar_expect_tx(full, 49152);
                    TRACE2(5, 8 + kk);
                    const int krow = slice3(kk) * 64;
#pragma unroll
                    for (int ch = 0; ch < 3; ch++) tma_load(dst + ch * 8192, &p.m[M_WG], j3 * 176 + ch * 64, krow, full);
#pragma unroll
                    for (int ch = 0; ch < 3; ch++) tma_load(dst + (3 + ch) * 8192, &p.m[M_WU], j3 * 176 + ch * 64, krow, full);
                    ph ^= 1u << slot;
                    slot += 3; if (slot == NB) slot = 0;
                }
                slot = 0;
#pragma unroll 1
                for (int t = 0; t < 12; t++) {
                    uint32_t full = sb + BAR_FULLB + 8 * slot, dst = sb + OFF_B + slot * 16384;
                    if (t >= NB || slot % 3 == 0) mbar_wait(sb + BAR_EMPTYB + 8 * slot, bit(ph, slot));
                    mbar_expect_tx(full, 16384);
                    const int krow = (((pi + t / 3) & 3) * 2 + rho) * 176 + (t % 3) * 64;
                    tma_load(dst, &p.m[M_WD], col2, krow, full);
                    tma_load(dst + 8192, &p.m[M_WD], col2 ^ 64, krow, full);
                    ph ^= 1u << slot;
                    if (++slot == NB) slot = 0;
                }
            }
        } else if (warp <= 2) {
            const int w = warp - 1;
            const uint32_t fullb = sb + BAR_FULLA + 8 * NA1 * w, emptyb = sb + BAR_EMPTYA + 8 * NA1 * w;
            const uint32_t pemptyb = sb + BAR_PEMPTYA + 8 * NA1 * w;
            const uint32_t abase = sb + OFF_A + w * (NA * 8192), stg = sb + BAR_STG + 64 * w;
            const int row0 = rb * 128 + w * 64;
            if (elect_one()) {
                uint32_t ph = 0x3f;
                const CUtensorMap* ma = &p.m[part1 ? M_WIM : M_WRE];
                int slot = 0, lap = 0;
                mbar_wait(sb + BAR_XARR, 0);
#pragma unroll 1
                for (int m = 0; m < 32; m++) {
                    mbar_wait(emptyb + 8 * slot, bit(ph, slot));
                    mbar_expect_tx(fullb + 8 * slot, 8192);
                    if ((m & 1) == rho) {
                        if (lap > 0) mbar_wait(pemptyb + 8 * slot, (lap - 1) & 1);
                        tma_load_mc(a_slot_addr(sb, w, slot), ma, m * 64, row0, fullb + 8 * slot);
                    }
                    if (w == 0) TRACE2(3, m);
                    ph ^= 1u << slot;
                    if (++slot == NA1) { slot = 0; lap++; }
                }
                auto load_a = [&](int sl, auto&& issue) {
                    mbar_wait(emptyb + 8 * sl, bit(ph, sl));
                    mbar_expect_tx(fullb + 8 * sl, 8192);
                    issue(abase + sl * 8192, fullb + 8 * sl);
                    ph ^= 1u << sl;
                };
                mbar_wait(stg, 0);
                tma_store(&p.m[M_PQ], abase + 2 * 8192, part1 * 512 + nt1 * 128, row0); bulk_commit();
                mbar_wait(stg + 8, 0);
                tma_store(&p.m[M_PQ], abase + 3 * 8192, part1 * 512 + nt1 * 128 + 64, row0);
                bulk_store(g_rs + ((part1 * 16 + rb) * 4 + nt1) * 128 + w * 64, sb + OFF_RSP + w * 256, 256);
                bulk_commit();
                if (w == 0) TRACE(43);
                bulk_wait_all();
                cnt_add(CN_1 + (rb * 2 + rho) * 2 + w);
                if (w == 0) TRACE(8);
                cnt_wait<0>(CN_1 + (rb * 2 + rho) * 2 + w, tag, 4);
                if (w == 0) TRACE(56);
                fence_async_global();
#pragma unroll 1
                for (int kk = 2; kk < 8; kk++) {
                    const int c = (pi + (kk >> 1)) & 3, col = (c >> 1) * 512 + ((c & 1) * 2 + rho) * 128 + (kk & 1) * 64;
                    load_a((kk - 2) & 3, [&](uint32_t dst, uint32_t bar) { tma_load(dst, &p.m[M_PQ], col, row0, bar); });
                }
                if (w == 0) TRACE(2);
                mbar_wait(stg + 16, 0);
                tma_store(&p.m[M_Z], abase + 3 * 8192, col2, row0); bulk_commit();
                bulk_wait_all();
                cnt_add(CN_2 + rb * 2 + w);
                if (w == 0) TRACE(11);
                mbar_wait(stg + 24, 0);
                bulk_store(g_stats + ((rb * 2 + w) * 8 + j3) * 64, sb + OFF_ST + w * 512, 512); bulk_commit();
                cnt_wait<0>(CN_2 + rb * 2 + w, tag, 8);
                if (w == 0) TRACE(57);
                fence_async_global();
#pragma unroll 1
                for (int kk = 1; kk < 8; kk++) {
                    const int sl = (kk - 1) & 3;
                    load_a(sl, [&](uint32_t dst, uint32_t bar) { tma_load(dst, &p.m[M_Z], slice3(kk) * 64, row0, bar); });
                    if (kk == 2) { bulk_wait_all(); cnt_add(CN_2S + rb * 2 + w); }
                    if (kk == 3) { cnt_wait<0>(CN_2S + rb * 2 + w, tag, 8); mbar_arrive(sb + BAR_DEP + 8 * w); }
                }
                if (w == 0) TRACE(3);
                uint8_t* hdst = g_h + (size_t)((rb * 2 + w) * 8 + j3) * 3 * 8192;
                mbar_wait(stg + 32, 0); bulk_store(hdst, abase + 3 * 8192, 8192); bulk_commit();
                mbar_wait(stg + 40, 0); bulk_store(hdst + 8192, abase + 0 * 8192, 8192); bulk_commit();
                mbar_wait(stg + 48, 0); bulk_store(hdst + 16384, abase + 1 * 8192, 8192); bulk_commit();
                bulk_wait_all();
                cnt_add(CN_3 + (rb * 2 + rho) * 2 + w);
                if (w == 0) TRACE(14);
                cnt_wait<0>(CN_3 + (rb * 2 + rho) * 2 + w, tag, 4);
                if (w == 0) TRACE(58);
                fence_async_global();
#pragma unroll 1
                for (int t = 3; t < 12; t++) {
                    const int jj = ((pi + t / 3) & 3) * 2 + rho;
                    const uint8_t* src = g_h + (size_t)(((rb * 2 + w) * 8 + jj) * 3 + t % 3) * 8192;
                    load_a((t - 1) & 3, [&](uint32_t dst, uint32_t bar) { bulk_load(dst, src, 8192, bar); });
                }
                if (w == 0) TRACE(4);
                mbar_wait(stg + 56, 0);
                tma_store(&p.m[M_OUT], abase, col2, row0); bulk_commit();
                asm volatile("cp.async.bulk.wait_group.read 0;" ::: "memory");
                if (w == 0) TRACE(17);
            }
        } else {
            if (lane == 0) cnt_wait<300>(CN_MOD + (b & 1), tag, NAUX);
            __syncwarp();
            {
                const float* md = g_mod;
                float t0[4], t1[6];
#pragma unroll
                for (int k = 0; k < 4; k++) t0[k] = __ldcg(md + 1 * 512 + nt1 * 128 + lane + 32 * k);
#pragma unroll
                for (int k = 0; k < 2; k++) {
                    const int col = col2 + lane + 32 * k;
                    t1[3 * k] = __ldcg(md + 2 * 512 + col); t1[3 * k + 1] = __ldcg(md + 4 * 512 + col); t1[3 * k + 2] = __ldcg(md + 5 * 512 + col);
                }
#pragma unroll
                for (int k = 0; k < 4; k++) sts_f(sb + OFF_CA1 + (lane + 32 * k) * 4, (part1 ? -1.f : 1.f) * bf_round(1.f + t0[k]));
#pragma unroll
                for (int k = 0; k < 2; k++) {
                    sts_f(sb + OFF_GA + (lane + 32 * k) * 4, t1[3 * k]); sts_f(sb + OFF_CB1 + (lane + 32 * k) * 4, bf_round(1.f + t1[3 * k + 1])); sts_f(sb + OFF_GB + (lane + 32 * k) * 4, t1[3 * k + 2]);
                }
                __syncwarp();
                if (lane == 0) { mbar_arrive(sb + BAR_AUX); TRACE(52); }
            }
            if (lane == 0) cnt_wait<300>(CN_V + (b & 1), tag, NAUX);
            __syncwarp();
            {
                float tr[4], ti[4];
#pragma unroll
                for (int k = 0; k < 4; k++) {
                    const int cidx = lane + 32 * k, col = (col2 ^ (cidx & 64)) + (cidx & 63);
                    tr[k] = __ldcg(g_v + col); ti[k] = __ldcg(g_v + 512 + col);
                }
#pragma unroll
                for (int k = 0; k < 4; k++) {
                    uint32_t rh, rl, ih, il;
                    split_bf16(tr[k], rh, rl); split_bf16(-ti[k], ih, il);
                    sts_u4(sb + OFF_SA + (lane + 32 * k) * 16, make_uint4(rh | (rl << 16), rh | (rl << 16), ih | (il << 16), ih | (il << 16)));
                }
                fence_async_smem();
                __syncwarp();
                if (lane == 0) { mbar_arrive(sb + BAR_AUX + 8); TRACE(53); }
            }
            if (lane == 0) cnt_wait<300>(CN_CS + (b & 1), tag, NAUX);
            __syncwarp();
            {
                float t[6][4];
#pragma unroll
                for (int k = 0; k < 6; k++) {
                    const int cidx = lane + 32 * k, f = j3 * 176 + cidx;
                    const bool ok = cidx < 176 && f < F_;
#pragma unroll
                    for (int q = 0; q < 4; q++) t[k][q] = ok ? __ldcg(g_cs + q * F_ + f) : 0.f;
                }
#pragma unroll
                for (int k = 0; k < 6; k++) {
                    const int cidx = lane + 32 * k;
                    if (cidx < 176) {
#pragma unroll
                        for (int m = 0; m < 2; m++) {
                            uint32_t ch, cl, bh, bl;
                            split_bf16(t[k][2 * m], ch, cl); split_bf16(t[k][2 * m + 1], bh, bl);
                            const uint32_t cw2 = ch | (cl << 16), bw2 = bh | (bl << 16);
                            sts_u4(sb + OFF_BX + (m * 176 + cidx) * 16, make_uint4(cw2, cw2, bw2, bw2));
                        }
                    }
                }
                fence_async_smem();
            }
            __syncwarp();
            if (lane == 0) { mbar_arrive(sb + BAR_AUX + 16); TRACE(50); }
        }
        __syncwarp();
        cluster_arrive();
        cluster_wait();
    } else {
        const int ct = tid - 128;
        const int w = (warp >> 2) - 1;
        const int wt = ct & 127;
        const int cw = warp - 4;
        {
            float f[2][16];
#pragma unroll
            for (int rr = 0; rr < 2; rr++) {
                const uint32_t u[8] = {xv[rr][0].x, xv[rr][0].y, xv[rr][0].z, xv[rr][0].w, xv[rr][1].x, xv[rr][1].y, xv[rr][1].z, xv[rr][1].w};
#pragma unroll
                for (int k = 0; k < 8; k++) { f[rr][2 * k] = bf_lo(u[k]); f[rr][2 * k + 1] = bf_hi(u[k]); }
            }
            float s0 = 0.f, s1 = 0.f;
#pragma unroll
            for (int k = 0; k < 16; k++) { s0 += f[0][k]; s1 += f[1][k]; }
#pragma unroll
            for (int o = 16; o > 0; o >>= 1) { s0 += __shfl_xor_sync(0xffffffffu, s0, o); s1 += __shfl_xor_sync(0xffffffffu, s1, o); }
            if (ct == 0) TRACE(24);
            if (lane == 0) mbar_arrive(sb + BAR_XARR);
            s0 *= (1.f / 512.f); s1 *= (1.f / 512.f);
            float v0 = 0.f, v1 = 0.f;
#pragma unroll
            for (int k = 0; k < 16; k++) { f[0][k] -= s0; v0 = fmaf(f[0][k], f[0][k], v0); f[1][k] -= s1; v1 = fmaf(f[1][k], f[1][k], v1); }
#pragma unroll
            for (int o = 16; o > 0; o >>= 1) { v0 += __shfl_xor_sync(0xffffffffu, v0, o); v1 += __shfl_xor_sync(0xffffffffu, v1, o); }
            const float rstd[2] = {rsqrtf(v0 * (1.f / 512.f) + 1e-5f), rsqrtf(v1 * (1.f / 512.f) + 1e-5f)};
            const uint32_t stg = sb + OFF_B + cw * 2048 + lane * 16;
#pragma unroll
            for (int rr = 0; rr < 2; rr++) {
                uint32_t o[8];
#pragma unroll
                for (int k = 0; k < 8; k++) o[k] = pack_bf16(f[rr][2 * k] * rstd[rr], f[rr][2 * k + 1] * rstd[rr]);
                sts_u4(stg + rr * 1024, make_uint4(o[0], o[1], o[2], o[3]));
                sts_u4(stg + rr * 1024 + 512, make_uint4(o[4], o[5], o[6], o[7]));
            }
            fence_async_smem();
            __syncwarp();
            if (elect_one()) {
                bulk_store(g_xn + (size_t)(b * 16 + cw * 2) * D_, sb + OFF_B + cw * 2048, 2048);
                bulk_commit();
                bulk_wait_all();
            }
            __syncwarp();
            if (ct == 0) TRACE(31);
            named_bar(1, 256);
            if (ct < 8) cnt_add(CN_X + ct);
            if (ct == 0) TRACE(5);
            cluster_wait();
        }
        reg_alloc<216>();
        const int cwarp = warp & 3;
        const int r0 = cwarp * 16 + (lane >> 2);
        const int c0 = (lane & 3) * 2;
        const uint32_t abase = sb + OFF_A + w * (NA * 8192);
        const uint32_t fullA = sb + BAR_FULLA + 8 * NA1 * w, emptyA = sb + BAR_EMPTYA + 8 * NA1 * w;
        const uint32_t peer_pemptyA = peer_sb + BAR_PEMPTYA + 8 * NA1 * w;
        const uint32_t fullB = sb + BAR_FULLB, emptyB = sb + BAR_EMPTYB, stgb = sb + BAR_STG + 64 * w;
        const int sm_row = cwarp * 16 + (lane & 7) + ((lane >> 3) & 1) * 8;
        const int sm_cg = lane >> 4;
        const uint32_t sm_off = sm_row * 128, sm_sw = sm_row & 7;
        uint32_t pha = 0, phb = 0;
        uint32_t stg_ev = 0;
        auto staged = [&]() { fence_async_smem(); named_bar(2 + w, 128); if (wt == 0) mbar_arrive(stgb + 8 * stg_ev); stg_ev++; };

        {
            float acc[64];
#pragma unroll
            for (int i = 0; i < 64; i++) acc[i] = 0.f;
            fence_regs(acc);
            float rsacc[4] = {0.f, 0.f, 0.f, 0.f};
            fence_regs(rsacc);
            const uint64_t d_ones = make_desc(sb + OFF_ONES, 16, 1024);
            int sa = 0, sbb = 0, psa = 0, psb = 0, kb = 0;
            auto step = [&](auto own) {
                mbar_wait(fullA + 8 * sa, bit(pha, sa));
                if (ct == 0) TRACE2(0, kb);
                mbar_wait(fullB + 8 * sbb, bit(phb, sbb));
                if (kb == 0 && ct == 0) TRACE(6);
                uint64_t da = make_desc(a_slot_addr(sb, w, sa), 16, 1024);
                uint64_t db = make_desc(sb + OFF_B + sbb * 16384, 8192, 1024);
                wgmma_fence();
#pragma unroll
                for (int k = 0; k < 4; k++) wgmma_n128<1>(acc, da + k * 2, db + k * 128, 1);
                if (decltype(own)::value) {
#pragma unroll
                    for (int k = 0; k < 4; k++) wgmma_n8<0>(rsacc, da + k * 2, d_ones, 1);
                }
                wgmma_commit();
                wgmma_wait<1>();
                if (kb > 0 && wt == 0) {
                    if (kb - 1 + NA1 < 32 && ((kb - 1) & 1) != rho) mbar_arrive_cl(peer_pemptyA + 8 * psa);
                    if (kb != 27 && kb != 28) mbar_arrive(emptyA + 8 * psa);
                    mbar_arrive(emptyB + 8 * psb);
                }
                pha ^= 1u << sa; phb ^= 1u << sbb;
                psa = sa; psb = sbb;
                if (++sa == NA1) sa = 0;
                if (++sbb == NB1) sbb = 0;
                kb++;
            };
            using Yes = BoolC<true>; using No = BoolC<false>;
#pragma unroll 1
            for (int i = 0; i < nt1; i++) step(No{});
#pragma unroll 1
            for (int g = 0; g < 7; g++) { step(Yes{}); step(No{}); step(No{}); step(No{}); }
            step(Yes{});
#pragma unroll 1
            for (int i = nt1; i < 3; i++) step(No{});
            wgmma_wait<0>();
            fence_regs(acc);
            if (wt == 0) { mbar_arrive(emptyB + 8 * 3); mbar_arrive(emptyA + 8 * 1); }
            if (ct == 0) TRACE(7);
            fence_regs(rsacc);
            if ((lane & 3) == 0) { sts_f(sb + OFF_RSP + (w * 64 + r0) * 4, rsacc[0]); sts_f(sb + OFF_RSP + (w * 64 + r0 + 8) * 4, rsacc[2]); }
            mbar_wait(sb + BAR_AUX, 0);
            const float2* ca1 = (const float2*)(smem_raw + OFF_CA1) + (lane & 3);
#pragma unroll
            for (int hf = 0; hf < 2; hf++) {
#pragma unroll
                for (int i = hf * 8; i < hf * 8 + 8; i += 2) {
                    const float2 c0v = ca1[i * 4], c1v = ca1[i * 4 + 4];
                    const float* a = &acc[i * 4];
                    const int cg = (i & 7) + sm_cg;
                    stsm4(abase + (2 + hf) * 8192 + sm_off + ((cg ^ sm_sw) << 4),
                          pack_bf16(a[0] * c0v.x, a[1] * c0v.y), pack_bf16(a[2] * c0v.x, a[3] * c0v.y), pack_bf16(a[4] * c1v.x, a[5] * c1v.y), pack_bf16(a[6] * c1v.x, a[7] * c1v.y));
                }
                staged();
            }
            if (ct == 0) TRACE(41);
        }
        {
            uint32_t xr[16];
            {
                const __nv_bfloat16* xp = p.x + (size_t)(rb * 128 + w * 64 + r0) * D_ + col2 + c0;
#pragma unroll
                for (int i = 0; i < 8; i++) {
                    xr[2 * i] = __ldg((const uint32_t*)(xp + i * 8));
                    xr[2 * i + 1] = __ldg((const uint32_t*)(xp + 8 * D_ + i * 8));
                }
            }
            float acc[64];
#pragma unroll
            for (int i = 0; i < 64; i++) acc[i] = 0.f;
            fence_regs(acc);
            float rpa[4], rpb[4];
            int psb = 0;
#pragma unroll 1
            for (int kk = 0; kk < 8; kk++) {
                const int sa = (kk + 2) & 3, sbb = (P2_SLOTS >> (4 * kk)) & 15;
                if (kk >= 2) { mbar_wait(fullA + 8 * sa, bit(pha, sa)); pha ^= 1u << sa; }
                mbar_wait(fullB + 8 * sbb, bit(phb, sbb));
                if (kk == 2 && ct == 0) TRACE(9);
                if (ct == 0) TRACE2(4, kk);
                if (kk == 2) {
#pragma unroll
                    for (int c = 0; c < 4; c++) {
                        const float* rp = g_rs + (((c >> 1) * 16 + rb) * 4 + (c & 1) * 2 + rho) * 128 + w * 64 + r0;
                        rpa[c] = __ldcg(rp); rpb[c] = __ldcg(rp + 8);
                    }
                }
                uint64_t da = make_desc(abase + sa * 8192, 16, 1024);
                uint64_t db = make_desc(sb + OFF_B + sbb * 16384, 16, 1024);
                wgmma_fence();
#pragma unroll
                for (int k = 0; k < 4; k++) wgmma_n128<0>(acc, da + k * 2, db + k * 2, 1);
                wgmma_commit();
                if (kk == 6) {
                    if ((lane & 3) < 2) {
                        const bool second = lane & 1;
                        uint32_t rh, rl, ih, il;
                        split_bf16(second ? rpb[0] + rpb[1] : rpa[0] + rpa[1], rh, rl); split_bf16(second ? rpb[2] + rpb[3] : rpa[2] + rpa[3], ih, il);
                        sts_u4(sb + OFF_AX + w * 1024 + (r0 + (second ? 8 : 0)) * 16, make_uint4(rh | (rh << 16), rl | (rl << 16), ih | (ih << 16), il | (il << 16)));
                    }
                    fence_async_smem();
                }
                wgmma_wait<1>();
                if (kk > 0 && wt == 0) {
                    if (kk - 1 < 4 || kk - 1 == 6) mbar_arrive(emptyA + 8 * ((kk + 1) & 3));
                    if (kk == 5) { mbar_expect_tx(sb + BAR_RFULL + 8 * w, 8192); mbar_arrive_cl(peer_sb + BAR_PRDY + 8 * w); }
                    mbar_arrive(emptyB + 8 * psb);
                }
                phb ^= 1u << sbb;
                psb = sbb;
            }
            {
                named_bar(2 + w, 128);
                mbar_wait(sb + BAR_AUX + 8, 0);
                wgmma_fence();
                wgmma_n128<0>(acc, make_desc_ns(sb + OFF_AX + w * 1024, OFF_ZERO - (OFF_AX + w * 1024), 128), make_desc_ns(sb + OFF_SA, 0, 128), 1);
                wgmma_commit();
            }
            wgmma_wait<0>();
            fence_regs(acc);
            if (wt == 0) { mbar_arrive(emptyB + 8 * psb); mbar_arrive(emptyA + 8 * 1); }
            if (ct == 0) TRACE(10);
            {
                uint32_t snd[16];
#pragma unroll
                for (int j = 0; j < 16; j++) snd[j] = pack_bf16(acc[32 + 2 * j], acc[33 + 2 * j]);
                mbar_wait(sb + BAR_PRDY + 8 * w, 0);
                const uint32_t rdst = peer_sb + OFF_A + w * (NA * 8192) + 2 * 8192 + wt * 16, rbar = peer_sb + BAR_RFULL + 8 * w;
#pragma unroll
                for (int j = 0; j < 4; j++) st_async4u(rdst + j * 2048, snd[4 * j], snd[4 * j + 1], snd[4 * j + 2], snd[4 * j + 3], rbar);
            }
            const float2* gap = (const float2*)(smem_raw + OFF_GA) + (lane & 3);
            const float2* cbp = (const float2*)(smem_raw + OFF_CB1) + (lane & 3);
            mbar_wait_cl(sb + BAR_RFULL + 8 * w, 0);
            if (ct == 0) TRACE(45);
            float s0 = 0.f, s1 = 0.f;
            uint32_t x2p[16];
            {
                uint32_t rcv[16], zz[16];
#pragma unroll
                for (int j = 0; j < 4; j++) { const uint4 r = lds_u4(abase + 2 * 8192 + j * 2048 + wt * 16); rcv[4 * j] = r.x; rcv[4 * j + 1] = r.y; rcv[4 * j + 2] = r.z; rcv[4 * j + 3] = r.w; }
#pragma unroll
                for (int j = 0; j < 8; j++) {
                    const float2 ga = gap[j * 4], cb = cbp[j * 4];
                    const float v0 = fmaf(ga.x, acc[4 * j] + bf_lo(rcv[2 * j]), bf_lo(xr[2 * j])), v1 = fmaf(ga.y, acc[4 * j + 1] + bf_hi(rcv[2 * j]), bf_hi(xr[2 * j]));
                    const float v2 = fmaf(ga.x, acc[4 * j + 2] + bf_lo(rcv[2 * j + 1]), bf_lo(xr[2 * j + 1])), v3 = fmaf(ga.y, acc[4 * j + 3] + bf_hi(rcv[2 * j + 1]), bf_hi(xr[2 * j + 1]));
                    x2p[2 * j] = pack_bf16(v0, v1); x2p[2 * j + 1] = pack_bf16(v2, v3);
                    acc[4 * j] = bf_lo(x2p[2 * j]); acc[4 * j + 1] = bf_hi(x2p[2 * j]);
                    acc[4 * j + 2] = bf_lo(x2p[2 * j + 1]); acc[4 * j + 3] = bf_hi(x2p[2 * j + 1]);
                    s0 += acc[4 * j] + acc[4 * j + 1]; s1 += acc[4 * j + 2] + acc[4 * j + 3];
                    zz[2 * j] = pack_bf16(acc[4 * j] * cb.x, acc[4 * j + 1] * cb.y);
                    zz[2 * j + 1] = pack_bf16(acc[4 * j + 2] * cb.x, acc[4 * j + 3] * cb.y);
                }
#pragma unroll
                for (int j = 0; j < 8; j += 2) {
                    const int cg = j + sm_cg;
                    stsm4(abase + 3 * 8192 + sm_off + ((cg ^ sm_sw) << 4), zz[2 * j], zz[2 * j + 1], zz[2 * j + 2], zz[2 * j + 3]);
                }
            }
            staged();
            if (wt == 0) mbar_arrive(emptyA + 8 * 2);
            s0 += __shfl_xor_sync(0xffffffffu, s0, 1); s1 += __shfl_xor_sync(0xffffffffu, s1, 1);
            s0 += __shfl_xor_sync(0xffffffffu, s0, 2); s1 += __shfl_xor_sync(0xffffffffu, s1, 2);
            float m0 = s0 * (1.f / 64.f), m1 = s1 * (1.f / 64.f), q0 = 0.f, q1 = 0.f;
#pragma unroll
            for (int j = 0; j < 8; j++) {
                float d0 = acc[4 * j] - m0, d1 = acc[4 * j + 1] - m0, d2 = acc[4 * j + 2] - m1, d3 = acc[4 * j + 3] - m1;
                q0 += d0 * d0 + d1 * d1; q1 += d2 * d2 + d3 * d3;
            }
            q0 += __shfl_xor_sync(0xffffffffu, q0, 1); q1 += __shfl_xor_sync(0xffffffffu, q1, 1);
            q0 += __shfl_xor_sync(0xffffffffu, q0, 2); q1 += __shfl_xor_sync(0xffffffffu, q1, 2);
            if ((lane & 3) == 0) {
                sts_f2(sb + OFF_ST + w * 512 + r0 * 8, m0, q0);
                sts_f2(sb + OFF_ST + w * 512 + (r0 + 8) * 8, m1, q1);
            }
            staged();
            uint4* xs = g_x2s + (size_t)(b * 2 + w) * 512 + wt;
#pragma unroll
            for (int j = 0; j < 4; j++) xs[j * 128] = make_uint4(x2p[4 * j], x2p[4 * j + 1], x2p[4 * j + 2], x2p[4 * j + 3]);
        }
        {
            float ag[88], au[88];
#pragma unroll
            for (int i = 0; i < 88; i++) { ag[i] = 0.f; au[i] = 0.f; }
            fence_regs(ag); fence_regs(au);
            float hg0 = 0.f, hg1 = 0.f;
            float2 st00, st01, st10, st11;
            int sbb = 3, psb = 0;
            int kk = 0;
            auto step3 = [&](auto stats) {
                const int sa = (kk + 3) & 3;
                if (kk >= 1) { mbar_wait(fullA + 8 * sa, bit(pha, sa)); pha ^= 1u << sa; }
                mbar_wait(fullB + 8 * sbb, bit(phb, sbb));
                if (kk == 1 && ct == 0) TRACE(12);
                if (ct == 0) TRACE2(4, 8 + kk);
                uint64_t da = make_desc(abase + sa * 8192, 16, 1024);
                uint64_t dg = make_desc(sb + OFF_B + sbb * 16384, 8192, 1024);
                uint64_t du = make_desc(sb + OFF_B + sbb * 16384 + 3 * 8192, 8192, 1024);
                wgmma_fence();
#pragma unroll
                for (int k = 0; k < 4; k++) {
                    wgmma_n176<1>(ag, da + k * 2, dg + k * 128, 1);
                    wgmma_n176<1>(au, da + k * 2, du + k * 128, 1);
                }
                wgmma_commit();
                if (decltype(stats)::value) {
                    float mu0 = st00.x + st01.x, mu1 = st10.x + st11.x;
                    mu0 += __shfl_xor_sync(0xffffffffu, mu0, 1); mu1 += __shfl_xor_sync(0xffffffffu, mu1, 1);
                    mu0 += __shfl_xor_sync(0xffffffffu, mu0, 2); mu1 += __shfl_xor_sync(0xffffffffu, mu1, 2);
                    mu0 *= 0.125f; mu1 *= 0.125f;
                    const float e0 = st00.x - mu0, e1 = st01.x - mu0, e2 = st10.x - mu1, e3 = st11.x - mu1;
                    float v0 = st00.y + st01.y + 64.f * (e0 * e0 + e1 * e1), v1 = st10.y + st11.y + 64.f * (e2 * e2 + e3 * e3);
                    v0 += __shfl_xor_sync(0xffffffffu, v0, 1); v1 += __shfl_xor_sync(0xffffffffu, v1, 1);
                    v0 += __shfl_xor_sync(0xffffffffu, v0, 2); v1 += __shfl_xor_sync(0xffffffffu, v1, 2);
                    v0 = v0 * (1.f / 512.f) + 1e-5f; v1 = v1 * (1.f / 512.f) + 1e-5f;
                    const float rs0 = rsqrtf(v0), rs1 = rsqrtf(v1);
                    hg0 = 0.5f * rs0; hg1 = 0.5f * rs1;
                    if ((lane & 3) < 2) {
                        const bool second = lane & 1;
                        uint32_t mh, ml, sh, sl2;
                        split_bf16(second ? -mu1 : -mu0, mh, ml); split_bf16(second ? v1 * rs1 : v0 * rs0, sh, sl2);
                        sts_u4(sb + OFF_AX + w * 1024 + (r0 + (second ? 8 : 0)) * 16, make_uint4(mh | (mh << 16), ml | (ml << 16), sh | (sh << 16), sl2 | (sl2 << 16)));
                    }
                    fence_async_smem();
                }
                wgmma_wait<1>();
                if (kk > 0 && wt == 0) {
                    if (kk - 1 < 4) mbar_arrive(emptyA + 8 * ((kk + 2) & 3));
                    mbar_arrive(emptyB + 8 * psb);
                }
                phb ^= 1u << sbb;
                psb = sbb;
                sbb += 3; if (sbb == NB) sbb = 0;
                kk++;
            };
#pragma unroll 1
            for (int i = 0; i < 4; i++) step3(BoolC<false>{});
            {
                mbar_wait(sb + BAR_DEP + 8 * w, 0);
                const float2* sp = g_stats + (size_t)((rb * 2 + w) * 8 + (lane & 3) * 2) * 64 + r0;
                st00 = __ldcg(sp); st01 = __ldcg(sp + 64); st10 = __ldcg(sp + 8); st11 = __ldcg(sp + 72);
            }
#pragma unroll 1
            for (int i = 0; i < 3; i++) step3(BoolC<false>{});
            step3(BoolC<true>{});
            {
                named_bar(2 + w, 128);
                mbar_wait(sb + BAR_AUX + 16, 0);
                const uint64_t dax = make_desc_ns(sb + OFF_AX + w * 1024, OFF_ZERO - (OFF_AX + w * 1024), 128);
                wgmma_fence();
                wgmma_n176<0>(ag, dax, make_desc_ns(sb + OFF_BX, 0, 128), 1);
                wgmma_n176<0>(au, dax, make_desc_ns(sb + OFF_BX + 176 * 16, 0, 128), 1);
                wgmma_commit();
            }
            wgmma_wait<0>();
            fence_regs(ag); fence_regs(au);
            if (wt == 0) { mbar_arrive(emptyB + 8 * psb); mbar_arrive(emptyA + 8 * 2); }
            if (ct == 0) TRACE(13);
            auto piece = [&](auto pcc) {
                constexpr int PC = decltype(pcc)::value;
                constexpr int I0 = PC * 8, I1 = PC < 2 ? PC * 8 + 8 : 22;
                constexpr int SLOT = (PC + 3) & 3;
#pragma unroll
                for (int i = I0; i < I1; i += 2) {
                    uint32_t rr[4];
#pragma unroll
                    for (int u = 0; u < 2; u++) {
                        const float* g = &ag[(i + u) * 4];
                        const float* uu = &au[(i + u) * 4];
                        const float h0 = fmaf(tanh_fast(hg0 * g[0]), hg0, hg0) * uu[0], h1 = fmaf(tanh_fast(hg0 * g[1]), hg0, hg0) * uu[1];
                        const float h2 = fmaf(tanh_fast(hg1 * g[2]), hg1, hg1) * uu[2], h3 = fmaf(tanh_fast(hg1 * g[3]), hg1, hg1) * uu[3];
                        rr[u * 2] = pack_bf16(h0, h1); rr[u * 2 + 1] = pack_bf16(h2, h3);
                    }
                    const int cg = (i & 7) + sm_cg;
                    stsm4(abase + SLOT * 8192 + sm_off + ((cg ^ sm_sw) << 4), rr[0], rr[1], rr[2], rr[3]);
                }
                staged();
            };
            piece(IntC<0>{}); piece(IntC<1>{}); piece(IntC<2>{});
            if (ct == 0) TRACE(47);
        }
        {
            uint4 xs4[4];
            {
                const uint4* xs = g_x2s + (size_t)(b * 2 + w) * 512 + wt;
#pragma unroll
                for (int j = 0; j < 4; j++) xs4[j] = __ldcg(xs + j * 128);
            }
            float acc[64];
#pragma unroll
            for (int i = 0; i < 64; i++) acc[i] = 0.f;
            fence_regs(acc);
            int sbb = 0, psb = 0, t = 0;
            auto step = [&](auto nk) {
                const int sa = (t + 3) & 3;
                if (t >= 3) { mbar_wait(fullA + 8 * sa, bit(pha, sa)); pha ^= 1u << sa; }
                mbar_wait(fullB + 8 * sbb, bit(phb, sbb));
                if (t == 3 && ct == 0) TRACE(15);
                if (ct == 0) TRACE2(4, 16 + t);
                uint64_t da = make_desc(abase + sa * 8192, 16, 1024);
                uint64_t db = make_desc(sb + OFF_B + sbb * 16384, 8192, 1024);
                wgmma_fence();
#pragma unroll
                for (int k = 0; k < decltype(nk)::value; k++) wgmma_n128<1>(acc, da + k * 2, db + k * 128, 1);
                wgmma_commit();
                wgmma_wait<1>();
                if (t > 0 && wt == 0) {
                    if (t - 1 < 8) mbar_arrive(emptyA + 8 * ((t + 2) & 3));
                    if (t == 9) { mbar_expect_tx(sb + BAR_RFULL + 8 * w, 8192); mbar_arrive_cl(peer_sb + BAR_PRDY + 8 * w); }
                    mbar_arrive(emptyB + 8 * psb);
                }
                phb ^= 1u << sbb;
                psb = sbb;
                if (++sbb == NB) sbb = 0;
                t++;
            };
#pragma unroll 1
            for (int blk = 0; blk < 4; blk++) { step(IntC<4>{}); step(IntC<4>{}); step(IntC<3>{}); }
            wgmma_wait<0>();
            fence_regs(acc);
            if (ct == 0) TRACE(16);
            {
                uint32_t snd[16];
#pragma unroll
                for (int j = 0; j < 16; j++) snd[j] = pack_bf16(acc[32 + 2 * j], acc[33 + 2 * j]);
                mbar_wait(sb + BAR_PRDY + 8 * w, 1);
                const uint32_t rdst = peer_sb + OFF_A + w * (NA * 8192) + 3 * 8192 + wt * 16, rbar = peer_sb + BAR_RFULL + 8 * w;
#pragma unroll
                for (int j = 0; j < 4; j++) st_async4u(rdst + j * 2048, snd[4 * j], snd[4 * j + 1], snd[4 * j + 2], snd[4 * j + 3], rbar);
            }
            const float2* gbp = (const float2*)(smem_raw + OFF_GB) + (lane & 3);
            mbar_wait_cl(sb + BAR_RFULL + 8 * w, 1);
            const uint32_t xp[16] = {xs4[0].x, xs4[0].y, xs4[0].z, xs4[0].w, xs4[1].x, xs4[1].y, xs4[1].z, xs4[1].w,
                                     xs4[2].x, xs4[2].y, xs4[2].z, xs4[2].w, xs4[3].x, xs4[3].y, xs4[3].z, xs4[3].w};
            uint32_t oo[16];
            {
                uint32_t rcv[16];
#pragma unroll
                for (int j = 0; j < 4; j++) { const uint4 r = lds_u4(abase + 3 * 8192 + j * 2048 + wt * 16); rcv[4 * j] = r.x; rcv[4 * j + 1] = r.y; rcv[4 * j + 2] = r.z; rcv[4 * j + 3] = r.w; }
#pragma unroll
                for (int j = 0; j < 8; j++) {
                    const float2 gb = gbp[j * 4];
                    oo[2 * j] = pack_bf16(fmaf(gb.x, acc[4 * j] + bf_lo(rcv[2 * j]), bf_lo(xp[2 * j])), fmaf(gb.y, acc[4 * j + 1] + bf_hi(rcv[2 * j]), bf_hi(xp[2 * j])));
                    oo[2 * j + 1] = pack_bf16(fmaf(gb.x, acc[4 * j + 2] + bf_lo(rcv[2 * j + 1]), bf_lo(xp[2 * j + 1])), fmaf(gb.y, acc[4 * j + 3] + bf_hi(rcv[2 * j + 1]), bf_hi(xp[2 * j + 1])));
                }
            }
#pragma unroll
            for (int j = 0; j < 8; j += 2) {
                const int cg = j + sm_cg;
                stsm4(abase + sm_off + ((cg ^ sm_sw) << 4), oo[2 * j], oo[2 * j + 1], oo[2 * j + 2], oo[2 * j + 3]);
            }
            staged();
        }
        named_bar(1, 256);
        if (ct == 0) {
            unsigned old = atomicInc(&g_done, NCTA + NAUX - 1);
            if (old == NCTA + NAUX - 1) g_epoch = tag;
        }
        cluster_arrive();
        cluster_wait();
    }
}

typedef CUresult (*EncodeFn)(CUtensorMap*, CUtensorMapDataType, cuuint32_t, void*, const cuuint64_t*, const cuuint64_t*, const cuuint32_t*,
                             const cuuint32_t*, CUtensorMapInterleave, CUtensorMapSwizzle, CUtensorMapL2promotion, CUtensorMapFloatOOBfill);

void make_map(EncodeFn enc, CUtensorMap* m, const void* ptr, uint64_t rows, uint64_t cols, uint32_t box_rows, uint32_t box_cols, bool swz) {
    cuuint64_t dims[2] = {cols, rows};
    cuuint64_t strides[1] = {cols * 2};
    cuuint32_t box[2] = {box_cols, box_rows};
    cuuint32_t es[2] = {1, 1};
    enc(m, CU_TENSOR_MAP_DATA_TYPE_BFLOAT16, 2, const_cast<void*>(ptr), dims, strides, box, es, CU_TENSOR_MAP_INTERLEAVE_NONE,
        swz ? CU_TENSOR_MAP_SWIZZLE_128B : CU_TENSOR_MAP_SWIZZLE_NONE, CU_TENSOR_MAP_L2_PROMOTION_L2_128B, CU_TENSOR_MAP_FLOAT_OOB_FILL_NONE);
}

}

extern "C" void kernel_launch(void* const* d_in, const int* in_sizes, int n_in, void* d_out, int out_size) {
    static EncodeFn enc = nullptr;
    static void *pxn, *ppq, *pz;
    if (!enc) {
        void* fn = nullptr;
        cudaDriverEntryPointQueryResult q;
        cudaGetDriverEntryPoint("cuTensorMapEncodeTiled", &fn, cudaEnableDefault, &q);
        enc = (EncodeFn)fn;
        cudaGetSymbolAddress(&pxn, g_xn);
        cudaGetSymbolAddress(&ppq, g_pq);
        cudaGetSymbolAddress(&pz, g_z);
        cudaFuncSetAttribute(mega_kernel, cudaFuncAttributeMaxDynamicSharedMemorySize, SMEM_BYTES);
    }
    Params p = {};
    p.x = (const __nv_bfloat16*)d_in[0];
    p.wre = (const __nv_bfloat16*)d_in[1];
    p.wim = (const __nv_bfloat16*)d_in[2];
    p.dr = (const __nv_bfloat16*)d_in[3];
    p.di = (const __nv_bfloat16*)d_in[4];
    p.wg = (const __nv_bfloat16*)d_in[6];
    p.wu = (const __nv_bfloat16*)d_in[7];
    p.wd = (const __nv_bfloat16*)d_in[8];
    p.c = (const __nv_bfloat16*)d_in[9];
    p.wmod = (const __nv_bfloat16*)d_in[10];
    make_map(enc, &p.m[M_WRE], d_in[1], S_, S_, 64, 64, true);
    make_map(enc, &p.m[M_WIM], d_in[2], S_, S_, 64, 64, true);
    make_map(enc, &p.m[M_XN], pxn, S_, D_, 64, 64, true);
    make_map(enc, &p.m[M_PQ], ppq, S_, 2 * D_, 64, 64, true);
    make_map(enc, &p.m[M_DR], d_in[3], D_, D_, 64, 64, true);
    make_map(enc, &p.m[M_DI], d_in[4], D_, D_, 64, 64, true);
    make_map(enc, &p.m[M_Z], pz, S_, D_, 64, 64, true);
    make_map(enc, &p.m[M_WG], d_in[6], D_, F_, 64, 64, true);
    make_map(enc, &p.m[M_WU], d_in[7], D_, F_, 64, 64, true);
    make_map(enc, &p.m[M_WD], d_in[8], F_, D_, 64, 64, true);
    make_map(enc, &p.m[M_OUT], d_out, S_, D_, 64, 64, true);
    make_map(enc, &p.m[M_WMODS], d_in[10], D_, 6 * D_, 64, 64, true);

    cudaLaunchConfig_t cfg = {};
    cfg.gridDim = dim3(NCTA + NAUX);
    cfg.blockDim = dim3(384);
    cfg.dynamicSmemBytes = SMEM_BYTES;
    cfg.stream = cudaStreamPerThread;
    cudaLaunchAttribute at[1];
    at[0].id = cudaLaunchAttributeClusterDimension;
    at[0].val.clusterDim.x = 2; at[0].val.clusterDim.y = 1; at[0].val.clusterDim.z = 1;
    cfg.attrs = at; cfg.numAttrs = 1;
    cudaLaunchKernelEx(&cfg, mega_kernel, p);
}
```

```cpp
#include <cuda_runtime.h>
#include <cuda_bf16.h>
#include <cuda.h>
#include <stdint.h>

namespace {

constexpr int S_ = 2048, D_ = 512, F_ = 1376;
constexpr int NCTA = 128;
constexpr int NAUX = 4;
constexpr int NB = 9;
constexpr int NA = 4;
constexpr int NA1 = 6;
constexpr int NB1 = 7;
constexpr uint32_t OFF_B = 0;
constexpr uint32_t OFF_A = NB * 16384;
constexpr uint32_t OFF_AUX = OFF_A + 2 * NA * 8192;
constexpr uint32_t OFF_ONES = OFF_AUX;
constexpr uint32_t OFF_CA1 = OFF_ONES + 1024;
constexpr uint32_t OFF_SA = OFF_CA1 + 128 * 4;
constexpr uint32_t OFF_GA = OFF_SA + 128 * 16;
constexpr uint32_t OFF_CB1 = OFF_GA + 64 * 4;
constexpr uint32_t OFF_GB = OFF_CB1 + 64 * 4;
constexpr uint32_t OFF_BX = OFF_GB + 64 * 4;
constexpr uint32_t OFF_AX = OFF_BX + 2 * 176 * 16;
constexpr uint32_t OFF_ZERO = OFF_AX + 2048;
constexpr uint32_t OFF_ST = OFF_ZERO + 1024;
constexpr uint32_t OFF_RSP = OFF_ST + 1024;
constexpr uint32_t OFF_BAR = OFF_RSP + 512;
constexpr uint32_t BAR_FULLB = OFF_BAR;
constexpr uint32_t BAR_EMPTYB = BAR_FULLB + 8 * NB;
constexpr uint32_t BAR_FULLA = BAR_EMPTYB + 8 * NB;
constexpr uint32_t BAR_EMPTYA = BAR_FULLA + 16 * NA1;
constexpr uint32_t BAR_PEMPTYA = BAR_EMPTYA + 16 * NA1;
constexpr uint32_t BAR_PRDY = BAR_PEMPTYA + 16 * NA1;
constexpr uint32_t BAR_RFULL = BAR_PRDY + 16;
constexpr uint32_t BAR_AUX = BAR_RFULL + 16;
constexpr uint32_t BAR_DEP = BAR_AUX + 24;
constexpr uint32_t BAR_STG = BAR_DEP + 16;
constexpr uint32_t BAR_XARR = BAR_STG + 128;
constexpr uint32_t SMEM_USED = BAR_XARR + 8;
constexpr uint32_t SMEM_BYTES = SMEM_USED;
static_assert(SMEM_BYTES <= 232448, "smem");
constexpr uint32_t P2_SLOTS = 4u | (5u << 4) | (6u << 8) | (0u << 12) | (7u << 16) | (8u << 20) | (1u << 24) | (2u << 28);

enum { M_WRE = 0, M_WIM, M_XN, M_PQ, M_DR, M_DI, M_Z, M_WG, M_WU, M_WD, M_OUT, M_WMODS, M_COUNT };

struct alignas(64) Params {
    const __nv_bfloat16* x;
    const __nv_bfloat16* c;
    const __nv_bfloat16* wmod;
    const __nv_bfloat16* wg;
    const __nv_bfloat16* wu;
    const __nv_bfloat16* dr;
    const __nv_bfloat16* di;
    const __nv_bfloat16* wd;
    const __nv_bfloat16* wre;
    const __nv_bfloat16* wim;
    const void* pad[6];
    CUtensorMap m[M_COUNT];
};

constexpr int CN_X = 0;
constexpr int CN_MOD = 8;
constexpr int CN_V = 10;
constexpr int CN_CS = 12;
constexpr int CN_1 = 16;
constexpr int CN_2 = CN_1 + 64;
constexpr int CN_3 = CN_2 + 32;
constexpr int CN_2S = CN_3 + 64;
constexpr int CN_COUNT = CN_2S + 32;

}

__device__ __align__(1024) __nv_bfloat16 g_xn[S_ * D_];
__device__ __align__(1024) __nv_bfloat16 g_pq[S_ * 2 * D_];
__device__ __align__(1024) __nv_bfloat16 g_z[S_ * D_];
__device__ __align__(1024) uint8_t g_h[32 * 8 * 3 * 8192];
__device__ __align__(1024) uint4 g_x2s[NCTA * 2 * 4 * 128];
__device__ __align__(1024) float2 g_stats[S_ * 8];
__device__ __align__(1024) float g_mod[6 * D_];
__device__ __align__(1024) float g_cs[4 * F_];
__device__ __align__(1024) float g_v[2 * D_];
__device__ __align__(1024) float g_rs[32 * 4 * 128];
__device__ __align__(1024) unsigned g_cnt[CN_COUNT * 32];
__device__ unsigned g_epoch;
__device__ unsigned g_done;
#define TRACE_INIT() do {} while (0)
#define TRACE(slot) do {} while (0)
#define TRACE2(ev, idx) do {} while (0)
#define TRACE_GT(slot) do {} while (0)

namespace {

__device__ __forceinline__ uint32_t smem_u32(const void* p) { return (uint32_t)__cvta_generic_to_shared(p); }
__device__ __forceinline__ void mbar_init(uint32_t bar, uint32_t cnt) { asm volatile("mbarrier.init.shared::cta.b64 [%0], %1;" :: "r"(bar), "r"(cnt) : "memory"); }
__device__ __forceinline__ void mbar_expect_tx(uint32_t bar, uint32_t bytes) { asm volatile("mbarrier.arrive.expect_tx.shared::cta.b64 _, [%0], %1;" :: "r"(bar), "r"(bytes) : "memory"); }
__device__ __forceinline__ void mbar_arrive(uint32_t bar) { asm volatile("mbarrier.arrive.shared::cta.b64 _, [%0];" :: "r"(bar) : "memory"); }
__device__ __forceinline__ uint32_t mapa(uint32_t addr, uint32_t cta) { uint32_t r; asm volatile("mapa.shared::cluster.u32 %0, %1, %2;" : "=r"(r) : "r"(addr), "r"(cta)); return r; }
__device__ __forceinline__ void mbar_arrive_cl(uint32_t cl_addr) { asm volatile("mbarrier.arrive.shared::cluster.b64 _, [%0];" :: "r"(cl_addr) : "memory"); }
__device__ __forceinline__ void mbar_wait(uint32_t bar, uint32_t parity) {
    asm volatile("{\n.reg .pred p;\n.reg .u32 c;\nmov.u32 c, 0;\n"
                 "MW_LOOP:\nmbarrier.try_wait.parity.shared::cta.b64 p, [%0], %1;\n@p bra MW_DONE;\n"
                 "add.u32 c, c, 1;\nsetp.lt.u32 p, c, 3000000;\n@p bra MW_LOOP;\ntrap;\nMW_DONE:\n}" :: "r"(bar), "r"(parity) : "memory");
}
__device__ __forceinline__ void mbar_wait_cl(uint32_t bar, uint32_t parity) {
    asm volatile("{\n.reg .pred p;\n.reg .u32 c;\nmov.u32 c, 0;\n"
                 "MW_LOOP:\nmbarrier.try_wait.parity.acquire.cluster.shared::cta.b64 p, [%0], %1;\n@p bra MW_DONE;\n"
                 "add.u32 c, c, 1;\nsetp.lt.u32 p, c, 3000000;\n@p bra MW_LOOP;\ntrap;\nMW_DONE:\n}" :: "r"(bar), "r"(parity) : "memory");
}
__device__ __forceinline__ void tma_load(uint32_t dst, const CUtensorMap* map, int c0, int c1, uint32_t bar) {
    asm volatile("cp.async.bulk.tensor.2d.shared::cluster.global.mbarrier::complete_tx::bytes [%0], [%1, {%3, %4}], [%2];"
                 :: "r"(dst), "l"(map), "r"(bar), "r"(c0), "r"(c1) : "memory");
}
__device__ __forceinline__ void tma_load_mc(uint32_t dst, const CUtensorMap* map, int c0, int c1, uint32_t bar) {
    asm volatile("cp.async.bulk.tensor.2d.shared::cluster.global.mbarrier::complete_tx::bytes.multicast::cluster [%0], [%1, {%3, %4}], [%2], %5;"
                 :: "r"(dst), "l"(map), "r"(bar), "r"(c0), "r"(c1), "h"((uint16_t)3) : "memory");
}
__device__ __forceinline__ void prefetch_tmap(const CUtensorMap* m) { asm volatile("prefetch.tensormap [%0];" :: "l"(m) : "memory"); }
__device__ __forceinline__ void bulk_prefetch(const void* p, uint32_t bytes) {
    asm volatile("cp.async.bulk.prefetch.L2.global [%0], %1;" :: "l"(p), "r"(bytes) : "memory");
}
__device__ __forceinline__ void tma_store(const CUtensorMap* map, uint32_t src, int c0, int c1) {
    asm volatile("cp.async.bulk.tensor.2d.global.shared::cta.bulk_group [%0, {%2, %3}], [%1];" :: "l"(map), "r"(src), "r"(c0), "r"(c1) : "memory");
}
__device__ __forceinline__ void bulk_commit() { asm volatile("cp.async.bulk.commit_group;" ::: "memory"); }
__device__ __forceinline__ void bulk_wait_all() { asm volatile("cp.async.bulk.wait_group 0;" ::: "memory"); }
__device__ __forceinline__ void fence_async_smem() { asm volatile("fence.proxy.async.shared::cta;" ::: "memory"); }
__device__ __forceinline__ void fence_async_global() { asm volatile("fence.proxy.async.global;" ::: "memory"); }
__device__ __forceinline__ bool elect_one() {
    uint32_t pred;
    asm volatile("{\n.reg .pred p;\nelect.sync _|p, 0xffffffff;\nselp.u32 %0, 1, 0, p;\n}" : "=r"(pred));
    return pred != 0;
}
__device__ __forceinline__ void cluster_arrive() { asm volatile("barrier.cluster.arrive.relaxed.aligned;" ::: "memory"); }
__device__ __forceinline__ void cluster_wait() { asm volatile("barrier.cluster.wait.aligned;" ::: "memory"); }
__device__ __forceinline__ void named_bar(int id, int n) { asm volatile("bar.sync %0, %1;" :: "r"(id), "r"(n) : "memory"); }
__device__ __forceinline__ void wgmma_fence() { asm volatile("wgmma.fence.sync.aligned;" ::: "memory"); }
__device__ __forceinline__ void wgmma_commit() { asm volatile("wgmma.commit_group.sync.aligned;" ::: "memory"); }
template <int N> __device__ __forceinline__ void wgmma_wait() { asm volatile("wgmma.wait_group.sync.aligned %0;" :: "n"(N) : "memory"); }
template <int R> __device__ __forceinline__ void reg_alloc() { asm volatile("setmaxnreg.inc.sync.aligned.u32 %0;" :: "n"(R)); }
template <int R> __device__ __forceinline__ void reg_dealloc() { asm volatile("setmaxnreg.dec.sync.aligned.u32 %0;" :: "n"(R)); }
__device__ __forceinline__ unsigned ld_relaxed(const unsigned* p) { unsigned v; asm volatile("ld.relaxed.gpu.global.u32 %0, [%1];" : "=r"(v) : "l"(p) : "memory"); return v; }
__device__ __forceinline__ void bulk_load(uint32_t dst, const void* g, uint32_t bytes, uint32_t bar) {
    asm volatile("cp.async.bulk.shared::cluster.global.mbarrier::complete_tx::bytes [%0], [%1], %2, [%3];" :: "r"(dst), "l"(g), "r"(bytes), "r"(bar) : "memory");
}
__device__ __forceinline__ void bulk_store(void* g, uint32_t src, uint32_t bytes) {
    asm volatile("cp.async.bulk.global.shared::cta.bulk_group [%0], [%1], %2;" :: "l"(g), "r"(src), "r"(bytes) : "memory");
}
__device__ __forceinline__ void sts_u4(uint32_t a, uint4 v) { asm volatile("st.shared.v4.u32 [%0], {%1, %2, %3, %4};" :: "r"(a), "r"(v.x), "r"(v.y), "r"(v.z), "r"(v.w) : "memory"); }
__device__ __forceinline__ void sts_f2(uint32_t a, float x, float y) { asm volatile("st.shared.v2.f32 [%0], {%1, %2};" :: "r"(a), "f"(x), "f"(y) : "memory"); }
__device__ __forceinline__ uint4 ldg_stream(const void* p) {
    uint4 v; asm volatile("ld.global.nc.L1::no_allocate.v4.u32 {%0, %1, %2, %3}, [%4];" : "=r"(v.x), "=r"(v.y), "=r"(v.z), "=r"(v.w) : "l"(p)); return v;
}
__device__ __forceinline__ uint64_t make_desc(uint32_t addr, uint32_t lbo, uint32_t sbo) {
    return (uint64_t)((addr & 0x3FFFF) >> 4) | ((uint64_t)(lbo >> 4) << 16) | ((uint64_t)(sbo >> 4) << 32) | ((uint64_t)1 << 62);
}
__device__ __forceinline__ uint64_t make_desc_ns(uint32_t addr, uint32_t lbo, uint32_t sbo) {
    return (uint64_t)((addr & 0x3FFFF) >> 4) | ((uint64_t)((lbo & 0x3FFFF) >> 4) << 16) | ((uint64_t)(sbo >> 4) << 32);
}
__device__ __forceinline__ uint32_t pack_bf16(float lo, float hi) {
    uint32_t r; asm("cvt.rn.bf16x2.f32 %0, %1, %2;" : "=r"(r) : "f"(hi), "f"(lo)); return r;
}
__device__ __forceinline__ float bf_lo(uint32_t v) { return __uint_as_float(v << 16); }
__device__ __forceinline__ float bf_hi(uint32_t v) { return __uint_as_float(v & 0xffff0000u); }
__device__ __forceinline__ void split_bf16(float v, uint32_t& hi, uint32_t& lo) {
    const __nv_bfloat16 h = __float2bfloat16_rn(v);
    hi = __bfloat16_as_ushort(h);
    lo = __bfloat16_as_ushort(__float2bfloat16_rn(v - __bfloat162float(h)));
}
__device__ __forceinline__ float bf_round(float v) { return __bfloat162float(__float2bfloat16_rn(v)); }
__device__ __forceinline__ void stsm4(uint32_t addr, uint32_t r0, uint32_t r1, uint32_t r2, uint32_t r3) {
    asm volatile("stmatrix.sync.aligned.m8n8.x4.shared.b16 [%0], {%1, %2, %3, %4};" :: "r"(addr), "r"(r0), "r"(r1), "r"(r2), "r"(r3));
}
__device__ __forceinline__ uint4 lds_u4(uint32_t a) { uint4 v; asm volatile("ld.shared.v4.u32 {%0, %1, %2, %3}, [%4];" : "=r"(v.x), "=r"(v.y), "=r"(v.z), "=r"(v.w) : "r"(a)); return v; }
__device__ __forceinline__ void sts_f(uint32_t a, float v) { asm volatile("st.shared.f32 [%0], %1;" :: "r"(a), "f"(v) : "memory"); }
__device__ __forceinline__ void st_async4u(uint32_t cl_addr, uint32_t a, uint32_t b, uint32_t c, uint32_t d, uint32_t cl_bar) {
    asm volatile("st.async.weak.shared::cluster.mbarrier::complete_tx::bytes.v4.b32 [%0], {%1, %2, %3, %4}, [%5];"
                 :: "r"(cl_addr), "r"(a), "r"(b), "r"(c), "r"(d), "r"(cl_bar) : "memory");
}
__device__ __forceinline__ float tanh_fast(float x) { float y; asm("tanh.approx.f32 %0, %1;" : "=f"(y) : "f"(x)); return y; }
template <int N> __device__ __forceinline__ void fence_regs(float (&a)[N]) {
#pragma unroll
    for (int i = 0; i < N; i++) asm volatile("" : "+f"(a[i]) :: "memory");
}
__device__ __forceinline__ void cnt_add(int idx) { asm volatile("red.relaxed.gpu.global.add.u32 [%0], 1;" :: "l"(g_cnt + idx * 32) : "memory"); }
template <int SLEEP_NS>
__device__ __forceinline__ void cnt_wait(int idx, unsigned tag, unsigned per) {
    const unsigned target = tag * per;
    const unsigned* c = g_cnt + idx * 32;
    unsigned it = 0;
    while ((int)(ld_relaxed(c) - target) < 0) {
        if (SLEEP_NS > 0) __nanosleep(SLEEP_NS);
        if (++it > 4000000u) __trap();
    }
    asm volatile("fence.acquire.gpu;" ::: "memory");
}

template <int TB>
__device__ __forceinline__ void wgmma_n128(float (&d)[64], uint64_t da, uint64_t db, int scale_d) {
    asm volatile("{\n.reg .pred p;\nsetp.ne.b32 p, %66, 0;\n"
        "wgmma.mma_async.sync.aligned.m64n128k16.f32.bf16.bf16 {"
        "%0, %1, %2, %3, %4, %5, %6, %7, %8, %9, %10, %11, %12, %13, %14, %15, "
        "%16, %17, %18, %19, %20, %21, %22, %23, %24, %25, %26, %27, %28, %29, %30, %31, "
        "%32, %33, %34, %35, %36, %37, %38, %39, %40, %41, %42, %43, %44, %45, %46, %47, "
        "%48, %49, %50, %51, %52, %53, %54, %55, %56, %57, %58, %59, %60, %61, %62, %63}, "
        "%64, %65, p, 1, 1, 0, %67;\n}"
        : "+f"(d[0]), "+f"(d[1]), "+f"(d[2]), "+f"(d[3]), "+f"(d[4]), "+f"(d[5]), "+f"(d[6]), "+f"(d[7]),
          "+f"(d[8]), "+f"(d[9]), "+f"(d[10]), "+f"(d[11]), "+f"(d[12]), "+f"(d[13]), "+f"(d[14]), "+f"(d[15]),
          "+f"(d[16]), "+f"(d[17]), "+f"(d[18]), "+f"(d[19]), "+f"(d[20]), "+f"(d[21]), "+f"(d[22]), "+f"(d[23]),
          "+f"(d[24]), "+f"(d[25]), "+f"(d[26]), "+f"(d[27]), "+f"(d[28]), "+f"(d[29]), "+f"(d[30]), "+f"(d[31]),
          "+f"(d[32]), "+f"(d[33]), "+f"(d[34]), "+f"(d[35]), "+f"(d[36]), "+f"(d[37]), "+f"(d[38]), "+f"(d[39]),
          "+f"(d[40]), "+f"(d[41]), "+f"(d[42]), "+f"(d[43]), "+f"(d[44]), "+f"(d[45]), "+f"(d[46]), "+f"(d[47]),
          "+f"(d[48]), "+f"(d[49]), "+f"(d[50]), "+f"(d[51]), "+f"(d[52]), "+f"(d[53]), "+f"(d[54]), "+f"(d[55]),
          "+f"(d[56]), "+f"(d[57]), "+f"(d[58]), "+f"(d[59]), "+f"(d[60]), "+f"(d[61]), "+f"(d[62]), "+f"(d[63])
        : "l"(da), "l"(db), "r"(scale_d), "n"(TB));
}
template <int TB>
__device__ __forceinline__ void wgmma_n176(float (&d)[88], uint64_t da, uint64_t db, int scale_d) {
    asm volatile("{\n.reg .pred p;\nsetp.ne.b32 p, %90, 0;\n"
        "wgmma.mma_async.sync.aligned.m64n176k16.f32.bf16.bf16 {"
        "%0, %1, %2, %3, %4, %5, %6, %7, %8, %9, %10, %11, %12, %13, %14, %15, "
        "%16, %17, %18, %19, %20, %21, %22, %23, %24, %25, %26, %27, %28, %29, %30, %31, "
        "%32, %33, %34, %35, %36, %37, %38, %39, %40, %41, %42, %43, %44, %45, %46, %47, "
        "%48, %49, %50, %51, %52, %53, %54, %55, %56, %57, %58, %59, %60, %61, %62, %63, "
        "%64, %65, %66, %67, %68, %69, %70, %71, %72, %73, %74, %75, %76, %77, %78, %79, "
        "%80, %81, %82, %83, %84, %85, %86, %87}, "
        "%88, %89, p, 1, 1, 0, %91;\n}"
        : "+f"(d[0]), "+f"(d[1]), "+f"(d[2]), "+f"(d[3]), "+f"(d[4]), "+f"(d[5]), "+f"(d[6]), "+f"(d[7]),
          "+f"(d[8]), "+f"(d[9]), "+f"(d[10]), "+f"(d[11]), "+f"(d[12]), "+f"(d[13]), "+f"(d[14]), "+f"(d[15]),
          "+f"(d[16]), "+f"(d[17]), "+f"(d[18]), "+f"(d[19]), "+f"(d[20]), "+f"(d[21]), "+f"(d[22]), "+f"(d[23]),
          "+f"(d[24]), "+f"(d[25]), "+f"(d[26]), "+f"(d[27]), "+f"(d[28]), "+f"(d[29]), "+f"(d[30]), "+f"(d[31]),
          "+f"(d[32]), "+f"(d[33]), "+f"(d[34]), "+f"(d[35]), "+f"(d[36]), "+f"(d[37]), "+f"(d[38]), "+f"(d[39]),
          "+f"(d[40]), "+f"(d[41]), "+f"(d[42]), "+f"(d[43]), "+f"(d[44]), "+f"(d[45]), "+f"(d[46]), "+f"(d[47]),
          "+f"(d[48]), "+f"(d[49]), "+f"(d[50]), "+f"(d[51]), "+f"(d[52]), "+f"(d[53]), "+f"(d[54]), "+f"(d[55]),
          "+f"(d[56]), "+f"(d[57]), "+f"(d[58]), "+f"(d[59]), "+f"(d[60]), "+f"(d[61]), "+f"(d[62]), "+f"(d[63]),
          "+f"(d[64]), "+f"(d[65]), "+f"(d[66]), "+f"(d[67]), "+f"(d[68]), "+f"(d[69]), "+f"(d[70]), "+f"(d[71]),
          "+f"(d[72]), "+f"(d[73]), "+f"(d[74]), "+f"(d[75]), "+f"(d[76]), "+f"(d[77]), "+f"(d[78]), "+f"(d[79]),
          "+f"(d[80]), "+f"(d[81]), "+f"(d[82]), "+f"(d[83]), "+f"(d[84]), "+f"(d[85]), "+f"(d[86]), "+f"(d[87])
        : "l"(da), "l"(db), "r"(scale_d), "n"(TB));
}
template <int TB>
__device__ __forceinline__ void wgmma_n8(float (&d)[4], uint64_t da, uint64_t db, int scale_d) {
    asm volatile("{\n.reg .pred p;\nsetp.ne.b32 p, %6, 0;\n"
        "wgmma.mma_async.sync.aligned.m64n8k16.f32.bf16.bf16 {"
        "%0, %1, %2, %3}, "
        "%4, %5, p, 1, 1, 0, %7;\n}"
        : "+f"(d[0]), "+f"(d[1]), "+f"(d[2]), "+f"(d[3])
        : "l"(da), "l"(db), "r"(scale_d), "n"(TB));
}
template <int TB>
__device__ __forceinline__ void wgmma_n256(float (&d)[128], uint64_t da, uint64_t db, int scale_d) {
    asm volatile("{\n.reg .pred p;\nsetp.ne.b32 p, %130, 0;\n"
        "wgmma.mma_async.sync.aligned.m64n256k16.f32.bf16.bf16 {"
        "%0, %1, %2, %3, %4, %5, %6, %7, %8, %9, %10, %11, %12, %13, %14, %15, "
        "%16, %17, %18, %19, %20, %21, %22, %23, %24, %25, %26, %27, %28, %29, %30, %31, "
        "%32, %33, %34, %35, %36, %37, %38, %39, %40, %41, %42, %43, %44, %45, %46, %47, "
        "%48, %49, %50, %51, %52, %53, %54, %55, %56, %57, %58, %59, %60, %61, %62, %63, "
        "%64, %65, %66, %67, %68, %69, %70, %71, %72, %73, %74, %75, %76, %77, %78, %79, "
        "%80, %81, %82, %83, %84, %85, %86, %87, %88, %89, %90, %91, %92, %93, %94, %95, "
        "%96, %97, %98, %99, %100, %101, %102, %103, %104, %105, %106, %107, %108, %109, %110, %111, "
        "%112, %113, %114, %115, %116, %117, %118, %119, %120, %121, %122, %123, %124, %125, %126, %127}, "
        "%128, %129, p, 1, 1, 0, %131;\n}"
        : "+f"(d[0]), "+f"(d[1]), "+f"(d[2]), "+f"(d[3]), "+f"(d[4]), "+f"(d[5]), "+f"(d[6]), "+f"(d[7]),
          "+f"(d[8]), "+f"(d[9]), "+f"(d[10]), "+f"(d[11]), "+f"(d[12]), "+f"(d[13]), "+f"(d[14]), "+f"(d[15]),
          "+f"(d[16]), "+f"(d[17]), "+f"(d[18]), "+f"(d[19]), "+f"(d[20]), "+f"(d[21]), "+f"(d[22]), "+f"(d[23]),
          "+f"(d[24]), "+f"(d[25]), "+f"(d[26]), "+f"(d[27]), "+f"(d[28]), "+f"(d[29]), "+f"(d[30]), "+f"(d[31]),
          "+f"(d[32]), "+f"(d[33]), "+f"(d[34]), "+f"(d[35]), "+f"(d[36]), "+f"(d[37]), "+f"(d[38]), "+f"(d[39]),
          "+f"(d[40]), "+f"(d[41]), "+f"(d[42]), "+f"(d[43]), "+f"(d[44]), "+f"(d[45]), "+f"(d[46]), "+f"(d[47]),
          "+f"(d[48]), "+f"(d[49]), "+f"(d[50]), "+f"(d[51]), "+f"(d[52]), "+f"(d[53]), "+f"(d[54]), "+f"(d[55]),
          "+f"(d[56]), "+f"(d[57]), "+f"(d[58]), "+f"(d[59]), "+f"(d[60]), "+f"(d[61]), "+f"(d[62]), "+f"(d[63]),
          "+f"(d[64]), "+f"(d[65]), "+f"(d[66]), "+f"(d[67]), "+f"(d[68]), "+f"(d[69]), "+f"(d[70]), "+f"(d[71]),
          "+f"(d[72]), "+f"(d[73]), "+f"(d[74]), "+f"(d[75]), "+f"(d[76]), "+f"(d[77]), "+f"(d[78]), "+f"(d[79]),
          "+f"(d[80]), "+f"(d[81]), "+f"(d[82]), "+f"(d[83]), "+f"(d[84]), "+f"(d[85]), "+f"(d[86]), "+f"(d[87]),
          "+f"(d[88]), "+f"(d[89]), "+f"(d[90]), "+f"(d[91]), "+f"(d[92]), "+f"(d[93]), "+f"(d[94]), "+f"(d[95]),
          "+f"(d[96]), "+f"(d[97]), "+f"(d[98]), "+f"(d[99]), "+f"(d[100]), "+f"(d[101]), "+f"(d[102]), "+f"(d[103]),
          "+f"(d[104]), "+f"(d[105]), "+f"(d[106]), "+f"(d[107]), "+f"(d[108]), "+f"(d[109]), "+f"(d[110]), "+f"(d[111]),
          "+f"(d[112]), "+f"(d[113]), "+f"(d[114]), "+f"(d[115]), "+f"(d[116]), "+f"(d[117]), "+f"(d[118]), "+f"(d[119]),
          "+f"(d[120]), "+f"(d[121]), "+f"(d[122]), "+f"(d[123]), "+f"(d[124]), "+f"(d[125]), "+f"(d[126]), "+f"(d[127])
        : "l"(da), "l"(db), "r"(scale_d), "n"(TB));
}

template <bool B> struct BoolC { static constexpr bool value = B; };
template <int I> struct IntC { static constexpr int value = I; };
__device__ __forceinline__ uint32_t bit(uint32_t mask, int i) { return (mask >> i) & 1u; }
__device__ __forceinline__ uint32_t a_slot_addr(uint32_t sb, int w, int slot) {
    return slot < NA ? sb + OFF_A + w * (NA * 8192) + slot * 8192 : sb + OFF_B + (7 + w) * 16384 + (slot - NA) * 8192;
}

constexpr int AX_NS = 5;
constexpr uint32_t AX_A = AX_NS * 32768;
constexpr uint32_t AX_OUT = AX_A + 3 * 8192;
constexpr uint32_t AX_BAR = AX_OUT + 6144;
__device__ __forceinline__ void aux_put_a(uint8_t* smem, int which, int row, int d, float v) {
    const int kb = d >> 6, c = d & 63;
    *(__nv_bfloat16*)(smem + AX_A + which * 8192 + kb * 1024 + row * 128 + (((c >> 3) ^ row) << 4) + (c & 7) * 2) = __float2bfloat16_rn(v);
}
__device__ __forceinline__ void aux_cta(const Params& p, uint8_t* smem, uint32_t sb, int a, unsigned tag, long long t_base_) {
    const int tid = threadIdx.x, lane = tid & 31;
    const int warp = __shfl_sync(0xffffffffu, tid >> 5, 0);
    if (tid == 0) {
        for (int s = 0; s < AX_NS; s++) { mbar_init(sb + AX_BAR + 8 * s, 1); mbar_init(sb + AX_BAR + 8 * (AX_NS + s), 1); }
        asm volatile("fence.mbarrier_init.release.cluster;" ::: "memory");
    }
    for (int i = tid; i < 3 * 8192 / 16; i += 384) *(uint4*)(smem + AX_A + i * 16) = make_uint4(0, 0, 0, 0);
    __syncthreads();
    if (warp == 0) {
        if (elect_one()) {
            const CUtensorMap* mw = &p.m[a < 2 ? M_WG : M_WU];
            const CUtensorMap* md = &p.m[a < 2 ? M_DR : M_DI];
            int slot = 0; uint32_t ph = 1;
#pragma unroll 1
            for (int st = 0; st < 48; st++) {
                const uint32_t full = sb + AX_BAR + 8 * slot, dst = sb + slot * 32768;
                mbar_wait(sb + AX_BAR + 8 * (AX_NS + slot), ph);
                mbar_expect_tx(full, 32768);
                const int kb = st & 7;
#pragma unroll
                for (int c = 0; c < 4; c++) {
                    if (st < 24) tma_load(dst + c * 8192, &p.m[M_WMODS], a * 768 + (st >> 3) * 256 + c * 64, kb * 64, full);
                    else if (st < 32) tma_load(dst + c * 8192, md, kb * 64, (a & 1) * 256 + c * 64, full);
                    else tma_load(dst + c * 8192, mw, (a & 1) * 688 + ((st - 32) >> 3) * 256 + c * 64, kb * 64, full);
                }
                if (++slot == AX_NS) { slot = 0; ph ^= 1; }
            }
        }
        return;
    }
    if (warp < 4) return;
    if (warp >= 8) {
        const int t = tid - 256, cg = t % 22, rq = t / 22;
        named_bar(2, 256);
        float* red = (float*)(smem + AX_OUT + 6144 + 256);
        if (rq < 4) {
            const __nv_bfloat16* W = (a < 2 ? p.wg : p.wu) + (size_t)(rq * 128) * F_ + (a & 1) * 688 + 512 + cg * 8;
            float cs[8], bi[8];
#pragma unroll
            for (int e = 0; e < 8; e++) { cs[e] = 0.f; bi[e] = 0.f; }
#pragma unroll 1
            for (int r0 = 0; r0 < 128; r0 += 16) {
                uint4 v[16]; float m1[16], m0[16];
#pragma unroll
                for (int k = 0; k < 16; k++) v[k] = ldg_stream(W + (size_t)(r0 + k) * F_);
#pragma unroll
                for (int k = 0; k < 4; k++) {
                    const float4 q1 = __ldcg((const float4*)(g_mod + 4 * 512 + rq * 128 + r0 + k * 4)), q0 = __ldcg((const float4*)(g_mod + 3 * 512 + rq * 128 + r0 + k * 4));
                    m1[4 * k] = q1.x; m1[4 * k + 1] = q1.y; m1[4 * k + 2] = q1.z; m1[4 * k + 3] = q1.w;
                    m0[4 * k] = q0.x; m0[4 * k + 1] = q0.y; m0[4 * k + 2] = q0.z; m0[4 * k + 3] = q0.w;
                }
#pragma unroll
                for (int k = 0; k < 16; k++) {
                    const float f[8] = {bf_lo(v[k].x), bf_hi(v[k].x), bf_lo(v[k].y), bf_hi(v[k].y), bf_lo(v[k].z), bf_hi(v[k].z), bf_lo(v[k].w), bf_hi(v[k].w)};
                    const float c1 = bf_round(1.f + m1[k]);
#pragma unroll
                    for (int e = 0; e < 8; e++) { cs[e] = fmaf(c1, f[e], cs[e]); bi[e] = fmaf(m0[k], f[e], bi[e]); }
                }
            }
#pragma unroll
            for (int e = 0; e < 8; e++) { red[(rq * 2 + 0) * 176 + cg * 8 + e] = cs[e]; red[(rq * 2 + 1) * 176 + cg * 8 + e] = bi[e]; }
        }
        named_bar(3, 128);
        float* outb = (float*)(smem + AX_OUT);
        for (int i = t; i < 352; i += 128) {
            const int row = i / 176, c = i % 176;
            outb[row * 768 + 512 + c] = (red[(0 + row) * 176 + c] + red[(2 + row) * 176 + c]) + (red[(4 + row) * 176 + c] + red[(6 + row) * 176 + c]);
        }
        fence_async_smem();
        named_bar(4, 256);
        return;
    }
    const int wt = tid - 128;
    for (int d = wt; d < 512; d += 128) {
        const float cval = __bfloat162float(p.c[d]);
        aux_put_a(smem, 0, 0, d, __fdividef(cval, 1.f + __expf(-cval)));
    }
    fence_async_smem();
    named_bar(1, 128);
    float* outb = (float*)(smem + AX_OUT);
    int slot = 0; uint32_t ph = 0;
    auto run_group = [&](auto kmaj, int which, int g0) {
        float acc[128];
#pragma unroll
        for (int i = 0; i < 128; i++) acc[i] = 0.f;
        fence_regs(acc);
        int pslot = 0;
#pragma unroll 1
        for (int kb = 0; kb < 8; kb++) {
            mbar_wait(sb + AX_BAR + 8 * slot, ph);
            const uint64_t da = make_desc(sb + AX_A + which * 8192 + kb * 1024, 16, 0);
            const uint64_t db = decltype(kmaj)::value ? make_desc(sb + slot * 32768, 16, 1024) : make_desc(sb + slot * 32768, 8192, 1024);
            wgmma_fence();
#pragma unroll
            for (int k = 0; k < 4; k++) {
                if (decltype(kmaj)::value) wgmma_n256<0>(acc, da + k * 2, db + k * 2, 1);
                else wgmma_n256<1>(acc, da + k * 2, db + k * 128, 1);
            }
            wgmma_commit();
            wgmma_wait<1>();
            if (kb > 0 && wt == 0) mbar_arrive(sb + AX_BAR + 8 * (AX_NS + pslot));
            pslot = slot;
            if (++slot == AX_NS) { slot = 0; ph ^= 1; }
        }
        wgmma_wait<0>();
        fence_regs(acc);
        if (wt == 0) mbar_arrive(sb + AX_BAR + 8 * (AX_NS + pslot));
        if (wt < 8) {
            const int row = wt >> 2, c0 = (wt & 3) * 2;
            if (row == 0 || which == 2) {
#pragma unroll
                for (int i = 0; i < 32; i++) {
                    const int c = g0 + i * 8 + c0;
                    const float v0 = which == 0 ? bf_round(acc[4 * i]) : acc[4 * i], v1 = which == 0 ? bf_round(acc[4 * i + 1]) : acc[4 * i + 1];
                    outb[row * 768 + c] = v0; outb[row * 768 + c + 1] = v1;
                }
            }
        }
    };
#pragma unroll 1
    for (int g = 0; g < 3; g++) run_group(BoolC<false>{}, 0, g * 256);
    {
        fence_async_smem();
        named_bar(1, 128);
        if (wt == 0) {
            bulk_store(g_mod + a * 768, sb + AX_OUT, 3072);
            bulk_commit(); bulk_wait_all();
            cnt_add(CN_MOD); cnt_add(CN_MOD + 1);
            TRACE(51);
            cnt_wait<0>(CN_MOD, tag, NAUX);
        }
        named_bar(1, 128);
        named_bar(2, 256);
        float t[3][4];
#pragma unroll
        for (int k = 0; k < 4; k++) { const int d = wt + 128 * k; t[0][k] = __ldcg(g_mod + d); t[1][k] = __ldcg(g_mod + 4 * 512 + d); t[2][k] = __ldcg(g_mod + 3 * 512 + d); }
#pragma unroll
        for (int k = 0; k < 4; k++) { const int d = wt + 128 * k; aux_put_a(smem, 1, 0, d, t[0][k]); aux_put_a(smem, 2, 0, d, 1.f + t[1][k]); aux_put_a(smem, 2, 1, d, t[2][k]); }
        fence_async_smem();
        named_bar(1, 128);
    }
    run_group(BoolC<true>{}, 1, 0);
    {
        fence_async_smem();
        named_bar(1, 128);
        if (wt == 0) {
            bulk_store(g_v + a * 256, sb + AX_OUT, 1024);
            bulk_commit(); bulk_wait_all();
            cnt_add(CN_V); cnt_add(CN_V + 1);
            TRACE(53);
        }
        named_bar(1, 128);
    }
#pragma unroll 1
    for (int g = 0; g < 2; g++) run_group(BoolC<false>{}, 2, g * 256);
    fence_async_smem();
    named_bar(4, 256);
    if (wt == 0) {
        const int isu = a >> 1, col0 = (a & 1) * 688;
        bulk_store(g_cs + (isu * 2 + 0) * F_ + col0, sb + AX_OUT, 688 * 4);
        bulk_store(g_cs + (isu * 2 + 1) * F_ + col0, sb + AX_OUT + 768 * 4, 688 * 4);
        bulk_commit(); bulk_wait_all();
        cnt_add(CN_CS); cnt_add(CN_CS + 1);
        TRACE(54);
        unsigned old = atomicInc(&g_done, NCTA + NAUX - 1);
        if (old == NCTA + NAUX - 1) g_epoch = tag;
    }
}

__global__ void __launch_bounds__(384, 1) mega_kernel(const __grid_constant__ Params p) {
    extern __shared__ __align__(1024) uint8_t smem_raw[];
    TRACE_INIT();
    const int tid = threadIdx.x;
    const int b = blockIdx.x;
    const int lane = tid & 31;
    uint4 xv[2][2];
    if (tid >= 128 && b < NCTA) {
        const __nv_bfloat16* xr = p.x + (size_t)(b * 16 + ((tid - 128) >> 5) * 2) * D_ + lane * 8;
#pragma unroll
        for (int rr = 0; rr < 2; rr++) { xv[rr][0] = ldg_stream(xr + rr * D_); xv[rr][1] = ldg_stream(xr + rr * D_ + 256); }
    }
    const unsigned tag = ld_relaxed(&g_epoch) + 1;
    const uint32_t sb = smem_u32(smem_raw);
    if (sb & 1023u) __trap();
    if (b >= NCTA) {
        aux_cta(p, smem_raw, sb, b - NCTA, tag, 0);
        return;
    }
    const int warp = __shfl_sync(0xffffffffu, tid >> 5, 0);
    const int rho = b & 1;
    const int rb = b >> 3;
    const int pi = (b >> 1) & 3;
    const int part1 = pi >> 1, nt1 = (pi & 1) * 2 + rho;
    const int j3 = pi * 2 + rho;
    auto slice3 = [&](int kk) { return (j3 + kk) & 7; };
    const int col2 = pi * 128 + rho * 64;

    if (tid == 0) TRACE_GT(0);
    {
        constexpr int NBAR = (SMEM_USED - OFF_BAR) / 8;
        if (elect_one()) {
#pragma unroll 1
            for (int i = warp; i < NBAR; i += 12) {
                uint32_t a = OFF_BAR + 8 * i;
                uint32_t cnt = 1;
                if (a >= BAR_EMPTYB && a < BAR_FULLA) cnt = 2;
                else if (a == BAR_XARR) cnt = 8;
                mbar_init(sb + a, cnt);
            }
            asm volatile("fence.mbarrier_init.release.cluster;" ::: "memory");
        }
    }
    if (warp == 2 && lane < M_COUNT) prefetch_tmap(&p.m[lane]);
    if (warp == 3) {
#pragma unroll
        for (int k = 0; k < 2; k++) asm volatile("st.shared.v4.u32 [%0], {%1, %1, %1, %1};" :: "r"(sb + OFF_ONES + (lane + 32 * k) * 16), "r"(0x3f803f80u) : "memory");
#pragma unroll
        for (int k = 0; k < 2; k++) asm volatile("st.shared.v4.u32 [%0], {%1, %1, %1, %1};" :: "r"(sb + OFF_ZERO + (lane + 32 * k) * 16), "r"(0u) : "memory");
        fence_async_smem();
    }
    const uint32_t peer_sb = mapa(sb, rho ^ 1);
    __syncthreads();
    cluster_arrive();

    if (warp < 4) {
        cluster_wait();
        if (tid == 0) TRACE(33);
        reg_dealloc<72>();
        if (warp == 0) {
            if (elect_one()) {
                cnt_wait<0>(CN_X + ((b >> 1) & 7), tag, 128);
                fence_async_global();
                uint32_t ph = 0x1ff;
                TRACE(1);
                int slot = 0;
#pragma unroll 1
                for (int kb = 0; kb < 32; kb++) {
                    uint32_t full = sb + BAR_FULLB + 8 * slot, dst = sb + OFF_B + slot * 16384;
                    mbar_wait(sb + BAR_EMPTYB + 8 * slot, bit(ph, slot));
                    TRACE2(6, kb);
                    mbar_expect_tx(full, 16384);
                    tma_load(dst, &p.m[M_XN], nt1 * 128, kb * 64, full);
                    tma_load(dst + 8192, &p.m[M_XN], nt1 * 128 + 64, kb * 64, full);
                    if (kb == 4) { bulk_prefetch((const char*)p.dr + (size_t)b * 4096, 4096); bulk_prefetch((const char*)p.di + (size_t)b * 4096, 4096); }
                    if (kb == 10) bulk_prefetch((const char*)p.wg + (size_t)b * 11008, 11008);
                    if (kb == 16) bulk_prefetch((const char*)p.wu + (size_t)b * 11008, 11008);
                    if (kb == 26) bulk_prefetch((const char*)p.wd + (size_t)b * 11008, 11008);
                    ph ^= 1u << slot;
                    if (++slot == NB1) slot = 0;
                }
#pragma unroll 1
                for (int kk = 0; kk < 8; kk++) {
                    slot = (P2_SLOTS >> (4 * kk)) & 15;
                    uint32_t full = sb + BAR_FULLB + 8 * slot, dst = sb + OFF_B + slot * 16384;
                    if (slot >= 7) {
                        mbar_wait(sb + BAR_EMPTYA + 8 * (NA1 * (slot - 7) + 4), 0);
                        mbar_wait(sb + BAR_EMPTYA + 8 * (NA1 * (slot - 7) + 5), 0);
                    } else {
                        mbar_wait(sb + BAR_EMPTYB + 8 * slot, bit(ph, slot));
                    }
                    mbar_expect_tx(full, 16384);
                    const int c = (pi + (kk >> 1)) & 3, kcol = ((c & 1) * 2 + rho) * 128 + (kk & 1) * 64;
                    const CUtensorMap* md = &p.m[(c >> 1) ? M_DI : M_DR];
                    tma_load(dst, md, kcol, col2, full);
                    tma_load(dst + 8192, md, kcol, col2 ^ 64, full);
                    ph ^= 1u << slot;
                }
                {
                    const unsigned old = atomicInc(&g_done, NCTA + NAUX - 1);
                    if (old == NCTA + NAUX - 1) g_epoch = tag;
                }
                slot = 3;
#pragma unroll 1
                for (int kk = 0; kk < 8; kk++) {
                    uint32_t dst = sb + OFF_B + slot * 16384;
                    uint32_t full = sb + BAR_FULLB + 8 * slot;
                    mbar_wait(sb + BAR_EMPTYB + 8 * slot, bit(ph, slot));
                    if (kk < 3) { mbar_wait(sb + BAR_EMPTYB + 8 * (slot + 1), bit(ph, slot + 1)); mbar_wait(sb + BAR_EMPTYB + 8 * (slot + 2), bit(ph, slot + 2)); }
                    mbar_expect_tx(full, 49152);
                    TRACE2(5, 8 + kk);
                    const int krow = slice3(kk) * 64;
#pragma unroll
                    for (int ch = 0; ch < 3; ch++) tma_load(dst + ch * 8192, &p.m[M_WG], j3 * 176 + ch * 64, krow, full);
#pragma unroll
                    for (int ch = 0; ch < 3; ch++) tma_load(dst + (3 + ch) * 8192, &p.m[M_WU], j3 * 176 + ch * 64, krow, full);
                    ph ^= 1u << slot;
                    slot += 3; if (slot == NB) slot = 0;
                }
                slot = 0;
#pragma unroll 1
                for (int t = 0; t < 12; t++) {
                    uint32_t full = sb + BAR_FULLB + 8 * slot, dst = sb + OFF_B + slot * 16384;
                    if (t >= NB || slot % 3 == 0) mbar_wait(sb + BAR_EMPTYB + 8 * slot, bit(ph, slot));
                    mbar_expect_tx(full, 16384);
                    const int krow = (((pi + t / 3) & 3) * 2 + rho) * 176 + (t % 3) * 64;
                    tma_load(dst, &p.m[M_WD], col2, krow, full);
                    tma_load(dst + 8192, &p.m[M_WD], col2 ^ 64, krow, full);
                    ph ^= 1u << slot;
                    if (++slot == NB) slot = 0;
                }
            }
        } else if (warp <= 2) {
            const int w = warp - 1;
            const uint32_t fullb = sb + BAR_FULLA + 8 * NA1 * w, emptyb = sb + BAR_EMPTYA + 8 * NA1 * w;
            const uint32_t pemptyb = sb + BAR_PEMPTYA + 8 * NA1 * w;
            const uint32_t abase = sb + OFF_A + w * (NA * 8192), stg = sb + BAR_STG + 64 * w;
            const int row0 = rb * 128 + w * 64;
            if (elect_one()) {
                uint32_t ph = 0x3f;
                const CUtensorMap* ma = &p.m[part1 ? M_WIM : M_WRE];
                int slot = 0, lap = 0;
                mbar_wait(sb + BAR_XARR, 0);
#pragma unroll 1
                for (int m = 0; m < 32; m++) {
                    mbar_wait(emptyb + 8 * slot, bit(ph, slot));
                    mbar_expect_tx(fullb + 8 * slot, 8192);
                    if ((m & 1) == rho) {
                        if (lap > 0) mbar_wait(pemptyb + 8 * slot, (lap - 1) & 1);
                        tma_load_mc(a_slot_addr(sb, w, slot), ma, m * 64, row0, fullb + 8 * slot);
                    }
                    if (w == 0) TRACE2(3, m);
                    ph ^= 1u << slot;
                    if (++slot == NA1) { slot = 0; lap++; }
                }
                auto load_a = [&](int sl, auto&& issue) {
                    mbar_wait(emptyb + 8 * sl, bit(ph, sl));
                    mbar_expect_tx(fullb + 8 * sl, 8192);
                    issue(abase + sl * 8192, fullb + 8 * sl);
                    ph ^= 1u << sl;
                };
                mbar_wait(stg, 0);
                tma_store(&p.m[M_PQ], abase + 2 * 8192, part1 * 512 + nt1 * 128, row0); bulk_commit();
                mbar_wait(stg + 8, 0);
                tma_store(&p.m[M_PQ], abase + 3 * 8192, part1 * 512 + nt1 * 128 + 64, row0);
                bulk_store(g_rs + ((part1 * 16 + rb) * 4 + nt1) * 128 + w * 64, sb + OFF_RSP + w * 256, 256);
                bulk_commit();
                if (w == 0) TRACE(43);
                bulk_wait_all();
                cnt_add(CN_1 + (rb * 2 + rho) * 2 + w);
                if (w == 0) TRACE(8);
                cnt_wait<0>(CN_1 + (rb * 2 + rho) * 2 + w, tag, 4);
                if (w == 0) TRACE(56);
                fence_async_global();
#pragma unroll 1
                for (int kk = 2; kk < 8; kk++) {
                    const int c = (pi + (kk >> 1)) & 3, col = (c >> 1) * 512 + ((c & 1) * 2 + rho) * 128 + (kk & 1) * 64;
                    load_a((kk - 2) & 3, [&](uint32_t dst, uint32_t bar) { tma_load(dst, &p.m[M_PQ], col, row0, bar); });
                }
                if (w == 0) TRACE(2);
                mbar_wait(stg + 16, 0);
                tma_store(&p.m[M_Z], abase + 3 * 8192, col2, row0); bulk_commit();
                bulk_wait_all();
                cnt_add(CN_2 + rb * 2 + w);
                if (w == 0) TRACE(11);
                mbar_wait(stg + 24, 0);
                bulk_store(g_stats + ((rb * 2 + w) * 8 + j3) * 64, sb + OFF_ST + w * 512, 512); bulk_commit();
                cnt_wait<0>(CN_2 + rb * 2 + w, tag, 8);
                if (w == 0) TRACE(57);
                fence_async_global();
#pragma unroll 1
                for (int kk = 1; kk < 8; kk++) {
                    const int sl = (kk - 1) & 3;
                    load_a(sl, [&](uint32_t dst, uint32_t bar) { tma_load(dst, &p.m[M_Z], slice3(kk) * 64, row0, bar); });
                    if (kk == 2) { bulk_wait_all(); cnt_add(CN_2S + rb * 2 + w); }
                    if (kk == 3) { cnt_wait<0>(CN_2S + rb * 2 + w, tag, 8); mbar_arrive(sb + BAR_DEP + 8 * w); }
                }
                if (w == 0) TRACE(3);
                uint8_t* hdst = g_h + (size_t)((rb * 2 + w) * 8 + j3) * 3 * 8192;
                mbar_wait(stg + 32, 0); bulk_store(hdst, abase + 3 * 8192, 8192); bulk_commit();
                mbar_wait(stg + 40, 0); bulk_store(hdst + 8192, abase + 0 * 8192, 8192); bulk_commit();
                mbar_wait(stg + 48, 0); bulk_store(hdst + 16384, abase + 1 * 8192, 8192); bulk_commit();
                bulk_wait_all();
                cnt_add(CN_3 + (rb * 2 + rho) * 2 + w);
                if (w == 0) TRACE(14);
                cnt_wait<0>(CN_3 + (rb * 2 + rho) * 2 + w, tag, 4);
                if (w == 0) TRACE(58);
                fence_async_global();
#pragma unroll 1
                for (int t = 3; t < 12; t++) {
                    const int jj = ((pi + t / 3) & 3) * 2 + rho;
                    const uint8_t* src = g_h + (size_t)(((rb * 2 + w) * 8 + jj) * 3 + t % 3) * 8192;
                    load_a((t - 1) & 3, [&](uint32_t dst, uint32_t bar) { bulk_load(dst, src, 8192, bar); });
                }
                if (w == 0) TRACE(4);
            }
        } else {
            if (lane == 0) cnt_wait<300>(CN_MOD + (b & 1), tag, NAUX);
            __syncwarp();
            {
                const float* md = g_mod;
                float t0[4], t1[6];
#pragma unroll
                for (int k = 0; k < 4; k++) t0[k] = __ldcg(md + 1 * 512 + nt1 * 128 + lane + 32 * k);
#pragma unroll
                for (int k = 0; k < 2; k++) {
                    const int col = col2 + lane + 32 * k;
                    t1[3 * k] = __ldcg(md + 2 * 512 + col); t1[3 * k + 1] = __ldcg(md + 4 * 512 + col); t1[3 * k + 2] = __ldcg(md + 5 * 512 + col);
                }
#pragma unroll
                for (int k = 0; k < 4; k++) sts_f(sb + OFF_CA1 + (lane + 32 * k) * 4, (part1 ? -1.f : 1.f) * bf_round(1.f + t0[k]));
#pragma unroll
                for (int k = 0; k < 2; k++) {
                    sts_f(sb + OFF_GA + (lane + 32 * k) * 4, t1[3 * k]); sts_f(sb + OFF_CB1 + (lane + 32 * k) * 4, bf_round(1.f + t1[3 * k + 1])); sts_f(sb + OFF_GB + (lane + 32 * k) * 4, t1[3 * k + 2]);
                }
                __syncwarp();
                if (lane == 0) { mbar_arrive(sb + BAR_AUX); TRACE(52); }
            }
            if (lane == 0) cnt_wait<300>(CN_V + (b & 1), tag, NAUX);
            __syncwarp();
            {
                float tr[4], ti[4];
#pragma unroll
                for (int k = 0; k < 4; k++) {
                    const int cidx = lane + 32 * k, col = (col2 ^ (cidx & 64)) + (cidx & 63);
                    tr[k] = __ldcg(g_v + col); ti[k] = __ldcg(g_v + 512 + col);
                }
#pragma unroll
                for (int k = 0; k < 4; k++) {
                    uint32_t rh, rl, ih, il;
                    split_bf16(tr[k], rh, rl); split_bf16(-ti[k], ih, il);
                    sts_u4(sb + OFF_SA + (lane + 32 * k) * 16, make_uint4(rh | (rl << 16), rh | (rl << 16), ih | (il << 16), ih | (il << 16)));
                }
                fence_async_smem();
                __syncwarp();
                if (lane == 0) { mbar_arrive(sb + BAR_AUX + 8); TRACE(53); }
            }
            if (lane == 0) cnt_wait<300>(CN_CS + (b & 1), tag, NAUX);
            __syncwarp();
            {
                float t[6][4];
#pragma unroll
                for (int k = 0; k < 6; k++) {
                    const int cidx = lane + 32 * k, f = j3 * 176 + cidx;
                    const bool ok = cidx < 176 && f < F_;
#pragma unroll
                    for (int q = 0; q < 4; q++) t[k][q] = ok ? __ldcg(g_cs + q * F_ + f) : 0.f;
                }
#pragma unroll
                for (int k = 0; k < 6; k++) {
                    const int cidx = lane + 32 * k;
                    if (cidx < 176) {
#pragma unroll
                        for (int m = 0; m < 2; m++) {
                            uint32_t ch, cl, bh, bl;
                            split_bf16(t[k][2 * m], ch, cl); split_bf16(t[k][2 * m + 1], bh, bl);
                            const uint32_t cw2 = ch | (cl << 16), bw2 = bh | (bl << 16);
                            sts_u4(sb + OFF_BX + (m * 176 + cidx) * 16, make_uint4(cw2, cw2, bw2, bw2));
                        }
                    }
                }
                fence_async_smem();
            }
            __syncwarp();
            if (lane == 0) { mbar_arrive(sb + BAR_AUX + 16); TRACE(50); }
        }
    } else {
        const int ct = tid - 128;
        const int w = (warp >> 2) - 1;
        const int wt = ct & 127;
        const int cw = warp - 4;
        {
            float f[2][16];
#pragma unroll
            for (int rr = 0; rr < 2; rr++) {
                const uint32_t u[8] = {xv[rr][0].x, xv[rr][0].y, xv[rr][0].z, xv[rr][0].w, xv[rr][1].x, xv[rr][1].y, xv[rr][1].z, xv[rr][1].w};
#pragma unroll
                for (int k = 0; k < 8; k++) { f[rr][2 * k] = bf_lo(u[k]); f[rr][2 * k + 1] = bf_hi(u[k]); }
            }
            float s0 = 0.f, s1 = 0.f;
#pragma unroll
            for (int k = 0; k < 16; k++) { s0 += f[0][k]; s1 += f[1][k]; }
#pragma unroll
            for (int o = 16; o > 0; o >>= 1) { s0 += __shfl_xor_sync(0xffffffffu, s0, o); s1 += __shfl_xor_sync(0xffffffffu, s1, o); }
            if (ct == 0) TRACE(24);
            if (lane == 0) mbar_arrive(sb + BAR_XARR);
            s0 *= (1.f / 512.f); s1 *= (1.f / 512.f);
            float v0 = 0.f, v1 = 0.f;
#pragma unroll
            for (int k = 0; k < 16; k++) { f[0][k] -= s0; v0 = fmaf(f[0][k], f[0][k], v0); f[1][k] -= s1; v1 = fmaf(f[1][k], f[1][k], v1); }
#pragma unroll
            for (int o = 16; o > 0; o >>= 1) { v0 += __shfl_xor_sync(0xffffffffu, v0, o); v1 += __shfl_xor_sync(0xffffffffu, v1, o); }
            const float rstd[2] = {rsqrtf(v0 * (1.f / 512.f) + 1e-5f), rsqrtf(v1 * (1.f / 512.f) + 1e-5f)};
            const uint32_t stg = sb + OFF_B + cw * 2048 + lane * 16;
#pragma unroll
            for (int rr = 0; rr < 2; rr++) {
                uint32_t o[8];
#pragma unroll
                for (int k = 0; k < 8; k++) o[k] = pack_bf16(f[rr][2 * k] * rstd[rr], f[rr][2 * k + 1] * rstd[rr]);
                sts_u4(stg + rr * 1024, make_uint4(o[0], o[1], o[2], o[3]));
                sts_u4(stg + rr * 1024 + 512, make_uint4(o[4], o[5], o[6], o[7]));
            }
            fence_async_smem();
            __syncwarp();
            if (elect_one()) {
                bulk_store(g_xn + (size_t)(b * 16 + cw * 2) * D_, sb + OFF_B + cw * 2048, 2048);
                bulk_commit();
                bulk_wait_all();
            }
            __syncwarp();
            if (ct == 0) TRACE(31);
            named_bar(1, 256);
            if (ct < 8) cnt_add(CN_X + ct);
            if (ct == 0) TRACE(5);
            cluster_wait();
        }
        reg_alloc<216>();
        const int cwarp = warp & 3;
        const int r0 = cwarp * 16 + (lane >> 2);
        const int c0 = (lane & 3) * 2;
        const uint32_t abase = sb + OFF_A + w * (NA * 8192);
        const uint32_t fullA = sb + BAR_FULLA + 8 * NA1 * w, emptyA = sb + BAR_EMPTYA + 8 * NA1 * w;
        const uint32_t peer_pemptyA = peer_sb + BAR_PEMPTYA + 8 * NA1 * w;
        const uint32_t fullB = sb + BAR_FULLB, emptyB = sb + BAR_EMPTYB, stgb = sb + BAR_STG + 64 * w;
        const int sm_row = cwarp * 16 + (lane & 7) + ((lane >> 3) & 1) * 8;
        const int sm_cg = lane >> 4;
        const uint32_t sm_off = sm_row * 128, sm_sw = sm_row & 7;
        uint32_t pha = 0, phb = 0;
        uint32_t stg_ev = 0;
        auto staged = [&]() { fence_async_smem(); named_bar(2 + w, 128); if (wt == 0) mbar_arrive(stgb + 8 * stg_ev); stg_ev++; };

        {
            float acc[64];
#pragma unroll
            for (int i = 0; i < 64; i++) acc[i] = 0.f;
            fence_regs(acc);
            float rsacc[4] = {0.f, 0.f, 0.f, 0.f};
            fence_regs(rsacc);
            const uint64_t d_ones = make_desc(sb + OFF_ONES, 16, 1024);
            int sa = 0, sbb = 0, psa = 0, psb = 0, kb = 0;
            auto step = [&](auto own) {
                mbar_wait(fullA + 8 * sa, bit(pha, sa));
                if (ct == 0) TRACE2(0, kb);
                mbar_wait(fullB + 8 * sbb, bit(phb, sbb));
                if (kb == 0 && ct == 0) TRACE(6);
                uint64_t da = make_desc(a_slot_addr(sb, w, sa), 16, 1024);
                uint64_t db = make_desc(sb + OFF_B + sbb * 16384, 8192, 1024);
                wgmma_fence();
#pragma unroll
                for (int k = 0; k < 4; k++) wgmma_n128<1>(acc, da + k * 2, db + k * 128, 1);
                if (decltype(own)::value) {
#pragma unroll
                    for (int k = 0; k < 4; k++) wgmma_n8<0>(rsacc, da + k * 2, d_ones, 1);
                }
                wgmma_commit();
                wgmma_wait<1>();
                if (kb > 0 && wt == 0) {
                    if (kb - 1 + NA1 < 32 && ((kb - 1) & 1) != rho) mbar_arrive_cl(peer_pemptyA + 8 * psa);
                    if (kb != 27 && kb != 28) mbar_arrive(emptyA + 8 * psa);
                    mbar_arrive(emptyB + 8 * psb);
                }
                pha ^= 1u << sa; phb ^= 1u << sbb;
                psa = sa; psb = sbb;
                if (++sa == NA1) sa = 0;
                if (++sbb == NB1) sbb = 0;
                kb++;
            };
            using Yes = BoolC<true>; using No = BoolC<false>;
#pragma unroll 1
            for (int i = 0; i < nt1; i++) step(No{});
#pragma unroll 1
            for (int g = 0; g < 7; g++) { step(Yes{}); step(No{}); step(No{}); step(No{}); }
            step(Yes{});
#pragma unroll 1
            for (int i = nt1; i < 3; i++) step(No{});
            wgmma_wait<0>();
            fence_regs(acc);
            if (wt == 0) { mbar_arrive(emptyB + 8 * 3); mbar_arrive(emptyA + 8 * 1); }
            if (ct == 0) TRACE(7);
            fence_regs(rsacc);
            if ((lane & 3) == 0) { sts_f(sb + OFF_RSP + (w * 64 + r0) * 4, rsacc[0]); sts_f(sb + OFF_RSP + (w * 64 + r0 + 8) * 4, rsacc[2]); }
            mbar_wait(sb + BAR_AUX, 0);
            const float2* ca1 = (const float2*)(smem_raw + OFF_CA1) + (lane & 3);
#pragma unroll
            for (int hf = 0; hf < 2; hf++) {
#pragma unroll
                for (int i = hf * 8; i < hf * 8 + 8; i += 2) {
                    const float2 c0v = ca1[i * 4], c1v = ca1[i * 4 + 4];
                    const float* a = &acc[i * 4];
                    const int cg = (i & 7) + sm_cg;
                    stsm4(abase + (2 + hf) * 8192 + sm_off + ((cg ^ sm_sw) << 4),
                          pack_bf16(a[0] * c0v.x, a[1] * c0v.y), pack_bf16(a[2] * c0v.x, a[3] * c0v.y), pack_bf16(a[4] * c1v.x, a[5] * c1v.y), pack_bf16(a[6] * c1v.x, a[7] * c1v.y));
                }
                staged();
            }
            if (ct == 0) TRACE(41);
        }
        {
            uint32_t xr[16];
            {
                const __nv_bfloat16* xp = p.x + (size_t)(rb * 128 + w * 64 + r0) * D_ + col2 + c0;
#pragma unroll
                for (int i = 0; i < 8; i++) {
                    xr[2 * i] = __ldg((const uint32_t*)(xp + i * 8));
                    xr[2 * i + 1] = __ldg((const uint32_t*)(xp + 8 * D_ + i * 8));
                }
            }
            float acc[64];
#pragma unroll
            for (int i = 0; i < 64; i++) acc[i] = 0.f;
            fence_regs(acc);
            float rpa[4], rpb[4];
            int psb = 0;
#pragma unroll 1
            for (int kk = 0; kk < 8; kk++) {
                const int sa = (kk + 2) & 3, sbb = (P2_SLOTS >> (4 * kk)) & 15;
                if (kk >= 2) { mbar_wait(fullA + 8 * sa, bit(pha, sa)); pha ^= 1u << sa; }
                mbar_wait(fullB + 8 * sbb, bit(phb, sbb));
                if (kk == 2 && ct == 0) TRACE(9);
                if (ct == 0) TRACE2(4, kk);
                if (kk == 2) {
#pragma unroll
                    for (int c = 0; c < 4; c++) {
                        const float* rp = g_rs + (((c >> 1) * 16 + rb) * 4 + (c & 1) * 2 + rho) * 128 + w * 64 + r0;
                        rpa[c] = __ldcg(rp); rpb[c] = __ldcg(rp + 8);
                    }
                }
                uint64_t da = make_desc(abase + sa * 8192, 16, 1024);
                uint64_t db = make_desc(sb + OFF_B + sbb * 16384, 16, 1024);
                wgmma_fence();
#pragma unroll
                for (int k = 0; k < 4; k++) wgmma_n128<0>(acc, da + k * 2, db + k * 2, 1);
                wgmma_commit();
                if (kk == 6) {
                    if ((lane & 3) < 2) {
                        const bool second = lane & 1;
                        uint32_t rh, rl, ih, il;
                        split_bf16(second ? rpb[0] + rpb[1] : rpa[0] + rpa[1], rh, rl); split_bf16(second ? rpb[2] + rpb[3] : rpa[2] + rpa[3], ih, il);
                        sts_u4(sb + OFF_AX + w * 1024 + (r0 + (second ? 8 : 0)) * 16, make_uint4(rh | (rh << 16), rl | (rl << 16), ih | (ih << 16), il | (il << 16)));
                    }
                    fence_async_smem();
                }
                wgmma_wait<1>();
                if (kk > 0 && wt == 0) {
                    if (kk - 1 < 4 || kk - 1 == 6) mbar_arrive(emptyA + 8 * ((kk + 1) & 3));
                    if (kk == 5) { mbar_expect_tx(sb + BAR_RFULL + 8 * w, 8192); mbar_arrive_cl(peer_sb + BAR_PRDY + 8 * w); }
                    mbar_arrive(emptyB + 8 * psb);
                }
                phb ^= 1u << sbb;
                psb = sbb;
            }
            {
                named_bar(2 + w, 128);
                mbar_wait(sb + BAR_AUX + 8, 0);
                wgmma_fence();
                wgmma_n128<0>(acc, make_desc_ns(sb + OFF_AX + w * 1024, OFF_ZERO - (OFF_AX + w * 1024), 128), make_desc_ns(sb + OFF_SA, 0, 128), 1);
                wgmma_commit();
            }
            wgmma_wait<0>();
            fence_regs(acc);
            if (wt == 0) { mbar_arrive(emptyB + 8 * psb); mbar_arrive(emptyA + 8 * 1); }
            if (ct == 0) TRACE(10);
            {
                uint32_t snd[16];
#pragma unroll
                for (int j = 0; j < 16; j++) snd[j] = pack_bf16(acc[32 + 2 * j], acc[33 + 2 * j]);
                mbar_wait(sb + BAR_PRDY + 8 * w, 0);
                const uint32_t rdst = peer_sb + OFF_A + w * (NA * 8192) + 2 * 8192 + wt * 16, rbar = peer_sb + BAR_RFULL + 8 * w;
#pragma unroll
                for (int j = 0; j < 4; j++) st_async4u(rdst + j * 2048, snd[4 * j], snd[4 * j + 1], snd[4 * j + 2], snd[4 * j + 3], rbar);
            }
            const float2* gap = (const float2*)(smem_raw + OFF_GA) + (lane & 3);
            const float2* cbp = (const float2*)(smem_raw + OFF_CB1) + (lane & 3);
            mbar_wait_cl(sb + BAR_RFULL + 8 * w, 0);
            if (ct == 0) TRACE(45);
            float s0 = 0.f, s1 = 0.f;
            uint32_t x2p[16];
            {
                uint32_t rcv[16], zz[16];
#pragma unroll
                for (int j = 0; j < 4; j++) { const uint4 r = lds_u4(abase + 2 * 8192 + j * 2048 + wt * 16); rcv[4 * j] = r.x; rcv[4 * j + 1] = r.y; rcv[4 * j + 2] = r.z; rcv[4 * j + 3] = r.w; }
#pragma unroll
                for (int j = 0; j < 8; j++) {
                    const float2 ga = gap[j * 4], cb = cbp[j * 4];
                    const float v0 = fmaf(ga.x, acc[4 * j] + bf_lo(rcv[2 * j]), bf_lo(xr[2 * j])), v1 = fmaf(ga.y, acc[4 * j + 1] + bf_hi(rcv[2 * j]), bf_hi(xr[2 * j]));
                    const float v2 = fmaf(ga.x, acc[4 * j + 2] + bf_lo(rcv[2 * j + 1]), bf_lo(xr[2 * j + 1])), v3 = fmaf(ga.y, acc[4 * j + 3] + bf_hi(rcv[2 * j + 1]), bf_hi(xr[2 * j + 1]));
                    x2p[2 * j] = pack_bf16(v0, v1); x2p[2 * j + 1] = pack_bf16(v2, v3);
                    acc[4 * j] = bf_lo(x2p[2 * j]); acc[4 * j + 1] = bf_hi(x2p[2 * j]);
                    acc[4 * j + 2] = bf_lo(x2p[2 * j + 1]); acc[4 * j + 3] = bf_hi(x2p[2 * j + 1]);
                    s0 += acc[4 * j] + acc[4 * j + 1]; s1 += acc[4 * j + 2] + acc[4 * j + 3];
                    zz[2 * j] = pack_bf16(acc[4 * j] * cb.x, acc[4 * j + 1] * cb.y);
                    zz[2 * j + 1] = pack_bf16(acc[4 * j + 2] * cb.x, acc[4 * j + 3] * cb.y);
                }
#pragma unroll
                for (int j = 0; j < 8; j += 2) {
                    const int cg = j + sm_cg;
                    stsm4(abase + 3 * 8192 + sm_off + ((cg ^ sm_sw) << 4), zz[2 * j], zz[2 * j + 1], zz[2 * j + 2], zz[2 * j + 3]);
                }
            }
            staged();
            if (wt == 0) mbar_arrive(emptyA + 8 * 2);
            s0 += __shfl_xor_sync(0xffffffffu, s0, 1); s1 += __shfl_xor_sync(0xffffffffu, s1, 1);
            s0 += __shfl_xor_sync(0xffffffffu, s0, 2); s1 += __shfl_xor_sync(0xffffffffu, s1, 2);
            float m0 = s0 * (1.f / 64.f), m1 = s1 * (1.f / 64.f), q0 = 0.f, q1 = 0.f;
#pragma unroll
            for (int j = 0; j < 8; j++) {
                float d0 = acc[4 * j] - m0, d1 = acc[4 * j + 1] - m0, d2 = acc[4 * j + 2] - m1, d3 = acc[4 * j + 3] - m1;
                q0 += d0 * d0 + d1 * d1; q1 += d2 * d2 + d3 * d3;
            }
            q0 += __shfl_xor_sync(0xffffffffu, q0, 1); q1 += __shfl_xor_sync(0xffffffffu, q1, 1);
            q0 += __shfl_xor_sync(0xffffffffu, q0, 2); q1 += __shfl_xor_sync(0xffffffffu, q1, 2);
            if ((lane & 3) == 0) {
                sts_f2(sb + OFF_ST + w * 512 + r0 * 8, m0, q0);
                sts_f2(sb + OFF_ST + w * 512 + (r0 + 8) * 8, m1, q1);
            }
            staged();
            uint4* xs = g_x2s + (size_t)(b * 2 + w) * 512 + wt;
#pragma unroll
            for (int j = 0; j < 4; j++) xs[j * 128] = make_uint4(x2p[4 * j], x2p[4 * j + 1], x2p[4 * j + 2], x2p[4 * j + 3]);
        }
        {
            float ag[88], au[88];
#pragma unroll
            for (int i = 0; i < 88; i++) { ag[i] = 0.f; au[i] = 0.f; }
            fence_regs(ag); fence_regs(au);
            float hg0 = 0.f, hg1 = 0.f;
            float2 st00, st01, st10, st11;
            int sbb = 3, psb = 0;
            int kk = 0;
            auto step3 = [&](auto stats) {
                const int sa = (kk + 3) & 3;
                if (kk >= 1) { mbar_wait(fullA + 8 * sa, bit(pha, sa)); pha ^= 1u << sa; }
                mbar_wait(fullB + 8 * sbb, bit(phb, sbb));
                if (kk == 1 && ct == 0) TRACE(12);
                if (ct == 0) TRACE2(4, 8 + kk);
                uint64_t da = make_desc(abase + sa * 8192, 16, 1024);
                uint64_t dg = make_desc(sb + OFF_B + sbb * 16384, 8192, 1024);
                uint64_t du = make_desc(sb + OFF_B + sbb * 16384 + 3 * 8192, 8192, 1024);
                wgmma_fence();
#pragma unroll
                for (int k = 0; k < 4; k++) {
                    wgmma_n176<1>(ag, da + k * 2, dg + k * 128, 1);
                    wgmma_n176<1>(au, da + k * 2, du + k * 128, 1);
                }
                wgmma_commit();
                if (decltype(stats)::value) {
                    float mu0 = st00.x + st01.x, mu1 = st10.x + st11.x;
                    mu0 += __shfl_xor_sync(0xffffffffu, mu0, 1); mu1 += __shfl_xor_sync(0xffffffffu, mu1, 1);
                    mu0 += __shfl_xor_sync(0xffffffffu, mu0, 2); mu1 += __shfl_xor_sync(0xffffffffu, mu1, 2);
                    mu0 *= 0.125f; mu1 *= 0.125f;
                    const float e0 = st00.x - mu0, e1 = st01.x - mu0, e2 = st10.x - mu1, e3 = st11.x - mu1;
                    float v0 = st00.y + st01.y + 64.f * (e0 * e0 + e1 * e1), v1 = st10.y + st11.y + 64.f * (e2 * e2 + e3 * e3);
                    v0 += __shfl_xor_sync(0xffffffffu, v0, 1); v1 += __shfl_xor_sync(0xffffffffu, v1, 1);
                    v0 += __shfl_xor_sync(0xffffffffu, v0, 2); v1 += __shfl_xor_sync(0xffffffffu, v1, 2);
                    v0 = v0 * (1.f / 512.f) + 1e-5f; v1 = v1 * (1.f / 512.f) + 1e-5f;
                    const float rs0 = rsqrtf(v0), rs1 = rsqrtf(v1);
                    hg0 = 0.5f * rs0; hg1 = 0.5f * rs1;
                    if ((lane & 3) < 2) {
                        const bool second = lane & 1;
                        uint32_t mh, ml, sh, sl2;
                        split_bf16(second ? -mu1 : -mu0, mh, ml); split_bf16(second ? v1 * rs1 : v0 * rs0, sh, sl2);
                        sts_u4(sb + OFF_AX + w * 1024 + (r0 + (second ? 8 : 0)) * 16, make_uint4(mh | (mh << 16), ml | (ml << 16), sh | (sh << 16), sl2 | (sl2 << 16)));
                    }
                    fence_async_smem();
                }
                wgmma_wait<1>();
                if (kk > 0 && wt == 0) {
                    if (kk - 1 < 4) mbar_arrive(emptyA + 8 * ((kk + 2) & 3));
                    mbar_arrive(emptyB + 8 * psb);
                }
                phb ^= 1u << sbb;
                psb = sbb;
                sbb += 3; if (sbb == NB) sbb = 0;
                kk++;
            };
#pragma unroll 1
            for (int i = 0; i < 4; i++) step3(BoolC<false>{});
            {
                mbar_wait(sb + BAR_DEP + 8 * w, 0);
                const float2* sp = g_stats + (size_t)((rb * 2 + w) * 8 + (lane & 3) * 2) * 64 + r0;
                st00 = __ldcg(sp); st01 = __ldcg(sp + 64); st10 = __ldcg(sp + 8); st11 = __ldcg(sp + 72);
            }
#pragma unroll 1
            for (int i = 0; i < 3; i++) step3(BoolC<false>{});
            step3(BoolC<true>{});
            {
                named_bar(2 + w, 128);
                mbar_wait(sb + BAR_AUX + 16, 0);
                const uint64_t dax = make_desc_ns(sb + OFF_AX + w * 1024, OFF_ZERO - (OFF_AX + w * 1024), 128);
                wgmma_fence();
                wgmma_n176<0>(ag, dax, make_desc_ns(sb + OFF_BX, 0, 128), 1);
                wgmma_n176<0>(au, dax, make_desc_ns(sb + OFF_BX + 176 * 16, 0, 128), 1);
                wgmma_commit();
            }
            wgmma_wait<0>();
            fence_regs(ag); fence_regs(au);
            if (wt == 0) { mbar_arrive(emptyB + 8 * psb); mbar_arrive(emptyA + 8 * 2); }
            if (ct == 0) TRACE(13);
            auto piece = [&](auto pcc) {
                constexpr int PC = decltype(pcc)::value;
                constexpr int I0 = PC * 8, I1 = PC < 2 ? PC * 8 + 8 : 22;
                constexpr int SLOT = (PC + 3) & 3;
#pragma unroll
                for (int i = I0; i < I1; i += 2) {
                    uint32_t rr[4];
#pragma unroll
                    for (int u = 0; u < 2; u++) {
                        const float* g = &ag[(i + u) * 4];
                        const float* uu = &au[(i + u) * 4];
                        const float h0 = fmaf(tanh_fast(hg0 * g[0]), hg0, hg0) * uu[0], h1 = fmaf(tanh_fast(hg0 * g[1]), hg0, hg0) * uu[1];
                        const float h2 = fmaf(tanh_fast(hg1 * g[2]), hg1, hg1) * uu[2], h3 = fmaf(tanh_fast(hg1 * g[3]), hg1, hg1) * uu[3];
                        rr[u * 2] = pack_bf16(h0, h1); rr[u * 2 + 1] = pack_bf16(h2, h3);
                    }
                    const int cg = (i & 7) + sm_cg;
                    stsm4(abase + SLOT * 8192 + sm_off + ((cg ^ sm_sw) << 4), rr[0], rr[1], rr[2], rr[3]);
                }
                staged();
            };
            piece(IntC<0>{}); piece(IntC<1>{}); piece(IntC<2>{});
            if (ct == 0) TRACE(47);
        }
        {
            uint4 xs4[4];
            {
                const uint4* xs = g_x2s + (size_t)(b * 2 + w) * 512 + wt;
#pragma unroll
                for (int j = 0; j < 4; j++) xs4[j] = __ldcg(xs + j * 128);
            }
            float acc[64];
#pragma unroll
            for (int i = 0; i < 64; i++) acc[i] = 0.f;
            fence_regs(acc);
            int sbb = 0, psb = 0, t = 0;
            auto step = [&](auto nk) {
                const int sa = (t + 3) & 3;
                if (t >= 3) { mbar_wait(fullA + 8 * sa, bit(pha, sa)); pha ^= 1u << sa; }
                mbar_wait(fullB + 8 * sbb, bit(phb, sbb));
                if (t == 3 && ct == 0) TRACE(15);
                if (ct == 0) TRACE2(4, 16 + t);
                uint64_t da = make_desc(abase + sa * 8192, 16, 1024);
                uint64_t db = make_desc(sb + OFF_B + sbb * 16384, 8192, 1024);
                wgmma_fence();
#pragma unroll
                for (int k = 0; k < decltype(nk)::value; k++) wgmma_n128<1>(acc, da + k * 2, db + k * 128, 1);
                wgmma_commit();
                wgmma_wait<1>();
                if (t > 0 && wt == 0) {
                    if (t - 1 < 8) mbar_arrive(emptyA + 8 * ((t + 2) & 3));
                    if (t == 9) { mbar_expect_tx(sb + BAR_RFULL + 8 * w, 8192); mbar_arrive_cl(peer_sb + BAR_PRDY + 8 * w); }
                    mbar_arrive(emptyB + 8 * psb);
                }
                phb ^= 1u << sbb;
                psb = sbb;
                if (++sbb == NB) sbb = 0;
                t++;
            };
#pragma unroll 1
            for (int blk = 0; blk < 4; blk++) { step(IntC<4>{}); step(IntC<4>{}); step(IntC<3>{}); }
            wgmma_wait<0>();
            fence_regs(acc);
            if (ct == 0) TRACE(16);
            {
                uint32_t snd[16];
#pragma unroll
                for (int j = 0; j < 16; j++) snd[j] = pack_bf16(acc[32 + 2 * j], acc[33 + 2 * j]);
                mbar_wait(sb + BAR_PRDY + 8 * w, 1);
                const uint32_t rdst = peer_sb + OFF_A + w * (NA * 8192) + 3 * 8192 + wt * 16, rbar = peer_sb + BAR_RFULL + 8 * w;
#pragma unroll
                for (int j = 0; j < 4; j++) st_async4u(rdst + j * 2048, snd[4 * j], snd[4 * j + 1], snd[4 * j + 2], snd[4 * j + 3], rbar);
            }
            const float2* gbp = (const float2*)(smem_raw + OFF_GB) + (lane & 3);
            mbar_wait_cl(sb + BAR_RFULL + 8 * w, 1);
            const uint32_t xp[16] = {xs4[0].x, xs4[0].y, xs4[0].z, xs4[0].w, xs4[1].x, xs4[1].y, xs4[1].z, xs4[1].w,
                                     xs4[2].x, xs4[2].y, xs4[2].z, xs4[2].w, xs4[3].x, xs4[3].y, xs4[3].z, xs4[3].w};
            uint32_t oo[16];
            {
                uint32_t rcv[16];
#pragma unroll
                for (int j = 0; j < 4; j++) { const uint4 r = lds_u4(abase + 3 * 8192 + j * 2048 + wt * 16); rcv[4 * j] = r.x; rcv[4 * j + 1] = r.y; rcv[4 * j + 2] = r.z; rcv[4 * j + 3] = r.w; }
#pragma unroll
                for (int j = 0; j < 8; j++) {
                    const float2 gb = gbp[j * 4];
                    oo[2 * j] = pack_bf16(fmaf(gb.x, acc[4 * j] + bf_lo(rcv[2 * j]), bf_lo(xp[2 * j])), fmaf(gb.y, acc[4 * j + 1] + bf_hi(rcv[2 * j]), bf_hi(xp[2 * j])));
                    oo[2 * j + 1] = pack_bf16(fmaf(gb.x, acc[4 * j + 2] + bf_lo(rcv[2 * j + 1]), bf_lo(xp[2 * j + 1])), fmaf(gb.y, acc[4 * j + 3] + bf_hi(rcv[2 * j + 1]), bf_hi(xp[2 * j + 1])));
                }
            }
#pragma unroll
            for (int j = 0; j < 8; j += 2) {
                const int cg = j + sm_cg;
                stsm4(abase + sm_off + ((cg ^ sm_sw) << 4), oo[2 * j], oo[2 * j + 1], oo[2 * j + 2], oo[2 * j + 3]);
            }
            fence_async_smem();
            named_bar(2 + w, 128);
            if (cwarp == 0 && elect_one()) {
                tma_store(&p.m[M_OUT], abase, col2, rb * 128 + w * 64);
                bulk_commit();
                asm volatile("cp.async.bulk.wait_group.read 0;" ::: "memory");
                if (w == 0) TRACE(17);
            }
        }
    }
}

typedef CUresult (*EncodeFn)(CUtensorMap*, CUtensorMapDataType, cuuint32_t, void*, const cuuint64_t*, const cuuint64_t*, const cuuint32_t*,
                             const cuuint32_t*, CUtensorMapInterleave, CUtensorMapSwizzle, CUtensorMapL2promotion, CUtensorMapFloatOOBfill);

void make_map(EncodeFn enc, CUtensorMap* m, const void* ptr, uint64_t rows, uint64_t cols, uint32_t box_rows, uint32_t box_cols, bool swz) {
    cuuint64_t dims[2] = {cols, rows};
    cuuint64_t strides[1] = {cols * 2};
    cuuint32_t box[2] = {box_cols, box_rows};
    cuuint32_t es[2] = {1, 1};
    enc(m, CU_TENSOR_MAP_DATA_TYPE_BFLOAT16, 2, const_cast<void*>(ptr), dims, strides, box, es, CU_TENSOR_MAP_INTERLEAVE_NONE,
        swz ? CU_TENSOR_MAP_SWIZZLE_128B : CU_TENSOR_MAP_SWIZZLE_NONE, CU_TENSOR_MAP_L2_PROMOTION_L2_128B, CU_TENSOR_MAP_FLOAT_OOB_FILL_NONE);
}

}

extern "C" void kernel_launch(void* const* d_in, const int* in_sizes, int n_in, void* d_out, int out_size) {
    static EncodeFn enc = nullptr;
    static void *pxn, *ppq, *pz;
    if (!enc) {
        void* fn = nullptr;
        cudaDriverEntryPointQueryResult q;
        cudaGetDriverEntryPoint("cuTensorMapEncodeTiled", &fn, cudaEnableDefault, &q);
        enc = (EncodeFn)fn;
        cudaGetSymbolAddress(&pxn, g_xn);
        cudaGetSymbolAddress(&ppq, g_pq);
        cudaGetSymbolAddress(&pz, g_z);
        cudaFuncSetAttribute(mega_kernel, cudaFuncAttributeMaxDynamicSharedMemorySize, SMEM_BYTES);
    }
    Params p = {};
    p.x = (const __nv_bfloat16*)d_in[0];
    p.wre = (const __nv_bfloat16*)d_in[1];
    p.wim = (const __nv_bfloat16*)d_in[2];
    p.dr = (const __nv_bfloat16*)d_in[3];
    p.di = (const __nv_bfloat16*)d_in[4];
    p.wg = (const __nv_bfloat16*)d_in[6];
    p.wu = (const __nv_bfloat16*)d_in[7];
    p.wd = (const __nv_bfloat16*)d_in[8];
    p.c = (const __nv_bfloat16*)d_in[9];
    p.wmod = (const __nv_bfloat16*)d_in[10];
    make_map(enc, &p.m[M_WRE], d_in[1], S_, S_, 64, 64, true);
    make_map(enc, &p.m[M_WIM], d_in[2], S_, S_, 64, 64, true);
    make_map(enc, &p.m[M_XN], pxn, S_, D_, 64, 64, true);
    make_map(enc, &p.m[M_PQ], ppq, S_, 2 * D_, 64, 64, true);
    make_map(enc, &p.m[M_DR], d_in[3], D_, D_, 64, 64, true);
    make_map(enc, &p.m[M_DI], d_in[4], D_, D_, 64, 64, true);
    make_map(enc, &p.m[M_Z], pz, S_, D_, 64, 64, true);
    make_map(enc, &p.m[M_WG], d_in[6], D_, F_, 64, 64, true);
    make_map(enc, &p.m[M_WU], d_in[7], D_, F_, 64, 64, true);
    make_map(enc, &p.m[M_WD], d_in[8], F_, D_, 64, 64, true);
    make_map(enc, &p.m[M_OUT], d_out, S_, D_, 64, 64, true);
    make_map(enc, &p.m[M_WMODS], d_in[10], D_, 6 * D_, 64, 64, true);

    cudaLaunchConfig_t cfg = {};
    cfg.gridDim = dim3(NCTA + NAUX);
    cfg.blockDim = dim3(384);
    cfg.dynamicSmemBytes = SMEM_BYTES;
    cfg.stream = cudaStreamPerThread;
    cudaLaunchAttribute at[1];
    at[0].id = cudaLaunchAttributeClusterDimension;
    at[0].val.clusterDim.x = 2; at[0].val.clusterDim.y = 1; at[0].val.clusterDim.z = 1;
    cfg.attrs = at; cfg.numAttrs = 1;
    cudaLaunchKernelEx(&cfg, mega_kernel, p);
}
```
